```python
import torch

def _softmax(x, axis=-1):
    return torch.softmax(x, dim=axis)

def _gelu(x):
    return torch.nn.functional.gelu(x, approximate='tanh')

def _silu(x):
    return torch.nn.functional.silu(x)

def _sigmoid(x):
    return torch.sigmoid(x)

def _layernorm(x, axis=-1, eps=1e-05):
    m = x.mean(dim=axis, keepdim=True)
    v = x.var(dim=axis, keepdim=True, unbiased=False)
    return (x - m) / torch.sqrt(v + eps)

def _scatter_add(tgt, idx, src, axis=0):
    return tgt.clone().index_add_(axis, idx, src)

def _segment_sum(src, seg, n):
    out = torch.zeros((n,) + src.shape[1:], dtype=src.dtype)
    return out.index_add_(0, seg, src)

def _pad(x, pw):
    flat = tuple((v for pair in reversed(pw) for v in pair))
    return torch.nn.functional.pad(x, flat)
kernel_name = 'adaLN_cond__sliding_block__mixer_channel_mlp__prompt'

def setup_inputs():

    _w = lambda a: (lambda t: t.to(torch.bfloat16) if t.is_floating_point() else t)(torch.as_tensor(a))

    def _A_setup():
        B, S, D = (1, 2048, 640)
        return {'x': _w((lambda *s: torch.randn(*s, dtype=torch.bfloat16) * 0.05)(B, S, D)), 'wqkv': _w((lambda *s: torch.randn(*s, dtype=torch.bfloat16) * 0.05)(D, 3 * D)), 'wo': _w((lambda *s: torch.randn(*s, dtype=torch.bfloat16) * 0.05)(D, D))}
    _A_in = _A_setup()

    def _B_setup():
        B, S, D, F = (1, 2048, 640, 1728)
        return {'x': _w((lambda *s: torch.randn(*s, dtype=torch.bfloat16) * 0.05)(B, S, D)), 'w1': _w((lambda *s: torch.randn(*s, dtype=torch.bfloat16) * 3.2)(D, F) * D ** (-0.5)), 'b1': _w((lambda *s: torch.randn(*s, dtype=torch.bfloat16) * 1.6)(F)), 'w2': _w((lambda *s: torch.randn(*s, dtype=torch.bfloat16) * 0.4)(F, D) * F ** (-0.5)), 'b2': _w((lambda *s: torch.randn(*s, dtype=torch.bfloat16) * 0.8)(D))}
    _B_in = _B_setup()
    return {'A_x': _A_in['x'], 'A_wqkv': _A_in['wqkv'], 'A_wo': _A_in['wo'], 'B_x': _B_in['x'], 'B_w1': _B_in['w1'], 'B_b1': _B_in['b1'], 'B_w2': _B_in['w2'], 'B_b2': _B_in['b2'], 'c': _w((lambda *s: torch.randn(*s, dtype=torch.bfloat16) * 0.1)(1, 640) * 8.0), 'w_mod': _w((lambda *s: torch.randn(*s, dtype=torch.bfloat16) * 0.1)(640, 6 * 640) * 640 ** (-0.5) * 8.0)}

def reference(A_x, A_wqkv, A_wo, B_x, B_w1, B_b1, B_w2, B_b2, c, w_mod):

    def _A_ref(x, wqkv, wo):
        B, S, D = x.shape
        H = 32
        Dh = D // H
        W = 256
        qkv = (lambda x, *d: x.permute(*d))((x @ wqkv).reshape(B, S, 3, H, Dh), 2, 0, 3, 1, 4)
        q, k, v = (qkv[0], qkv[1], qkv[2])
        scores = torch.einsum('bhqd,bhkd->bhqk', q, k) * Dh ** (-0.5)
        idx = torch.arange(S)
        mask = (idx[:, None] - idx[None, :] >= 0) & (idx[:, None] - idx[None, :] < W)
        scores = torch.where(mask[None, None], scores, -1000000000.0)
        p = _softmax(scores, axis=-1)
        o = torch.einsum('bhqk,bhkd->bhqd', p, v)
        return (lambda x, *d: x.permute(*d))(o, 0, 2, 1, 3).reshape(B, S, D) @ wo

    def _B_ref(x, w1, b1, w2, b2):
        y = _layernorm(x, axis=-1)
        h = _gelu(torch.einsum('bsd,df->bsf', y, w1) + b1)
        return torch.einsum('bsf,fd->bsd', h, w2) + b2
    x = A_x
    mod = (_silu(c) @ w_mod).reshape(c.shape[0], 6, 1, -1)
    sa, ca, ga, sb, cb, gb = (mod[:, 0].clone(), mod[:, 1].clone(), mod[:, 2].clone(), mod[:, 3].clone(), mod[:, 4].clone(), mod[:, 5].clone())
    h = _layernorm(x, axis=-1) * (1 + ca) + sa
    x = x + ga * _A_ref(h, A_wqkv, A_wo)
    h = _layernorm(x, axis=-1) * (1 + cb) + sb
    x = x + gb * _B_ref(h, B_w1, B_b1, B_w2, B_b2)
    return x
```

```cpp
#include <cuda_runtime.h>
#include <cuda.h>
#include <cuda_bf16.h>
#include <stdint.h>

namespace {

constexpr int SEQ = 2048, DM = 640, FF = 1728;

constexpr uint32_t OFF_RING = 163840;
constexpr uint32_t QKV_STAGE = 15360;
constexpr uint32_t W1_STAGE = 14336;
constexpr uint32_t W2_STAGE = 28672;
constexpr uint32_t HEAD_BYTES = 30720;
constexpr uint32_t SLOT_BYTES = 10240;
constexpr uint32_t OFF_WO = 122880;
constexpr uint32_t OFF_OSTG0 = 20480, OFF_OSTG1 = 81920;
constexpr uint32_t OFF_OSTG = 65536;
constexpr uint32_t OFF_STATSTG = 86016;
constexpr uint64_t OU = 0x3120643120ull;
constexpr uint32_t OFF_PIN = 0;
constexpr uint32_t OFF_PIN4 = 49152;
constexpr uint32_t OFF_PSTG = 65536;
constexpr uint32_t OFF_W2A = OFF_RING, OFF_W2B = OFF_RING + 2 * QKV_STAGE;
constexpr uint32_t OFF_W2C = 98304;
constexpr uint32_t OFF_W2D = 16384;
constexpr uint32_t OFF_FIN = 126976;
constexpr uint32_t OFF_GEMV = 7 * 16384;
constexpr uint32_t OFF_GEMV2 = 184320;
constexpr uint32_t OFF_AB = 225280;
constexpr uint32_t OFF_BAR = 230400;
constexpr uint32_t OFF_GA = 231424;
constexpr uint32_t OFF_B1 = 231744;
constexpr uint32_t OFF_CC = 232192;
constexpr uint32_t OFF_ROLE = 229632;
constexpr uint32_t OFF_GVP = OFF_CC;
constexpr uint32_t OFF_LIN = 228352;
constexpr uint32_t OFF_SC = OFF_LIN;
constexpr uint32_t SMEM_BYTES = 232448;

constexpr uint64_t QU_LO = 0xC3B02AD1CB0ADCBAull; constexpr uint32_t QU_HI = 0x2A41u;
constexpr uint64_t QD_LO = 0x8776554332110000ull; constexpr uint32_t QD_HI = 0xCBA9u;
constexpr uint64_t MU_LO = 0x0A32D1CB0A76DCBAull; constexpr uint32_t MU_HI = 0x51B4u;
constexpr uint64_t MD_LO = 0x8775433211000000ull; constexpr uint32_t MD_HI = 0xCBA9u;
__device__ __forceinline__ uint32_t nib(uint64_t lo, uint32_t hi, int s) { return (s < 16 ? (uint32_t)(lo >> (4 * s)) : hi >> (4 * s - 64)) & 15u; }
__device__ __forceinline__ uint32_t unit_off(uint32_t u) { return u < 10 ? u * 16384u : OFF_RING + (u - 10) * QKV_STAGE; }

enum : uint32_t {
  B_TILE = 0,
  B_RFULL = 10,
  B_GEMV = 18, B_GEMVDONE = 19, B_GVP = 20, B_PEERRDY = 21,
  B_H3 = 22,
  B_LATE = 24,
  B_REMPTY = 24,
  B_QKVDONE = 32, B_KVSTG = 33,
  B_HALO = 34,
  B_WO = 38, B_TAB2 = 39, B_OSTG = 40,
  B_OCONS = 68,
  B_OSTG1 = 41, B_H0DONE = 42, B_H2DONE = 43, B_KVSTG0 = 44,
  B_OPDONE = 45, B_X1STG = 46, B_MLP1DONE = 47, B_H3CONS = 48,
  B_PSTG = 49,
  B_PFREE = 53,
  B_PIN = 55,
  B_FIN = 59, B_OUTSTG = 60, B_W2D = 61, B_GEMV2DONE = 62, B_KVDONE = 63,
  B_XOWN = 64, B_STATS = 65, B_GEMV2 = 66,
  B_COUNT = 73,
  B_ROLE = 73
};

constexpr int FS = 32;
struct Scratch {
  uint8_t kv[128 * 4 * SLOT_BYTES];
  __nv_bfloat16 o[SEQ * DM];
  __nv_bfloat16 x1[SEQ * DM];
  float stats[128 * 128 * 8];
  uint8_t part[128 * 3 * 16384];
  uint8_t part4[128 * 16384];
  uint32_t epoch[128 * FS];
  uint32_t claim[64 * FS];
  uint32_t modw[3840];
  uint32_t kvflag[128 * FS];
  uint32_t oflag[32 * FS];
  uint32_t x1flag[16 * FS];
  uint32_t pflag[128 * FS];
  uint32_t p4flag[32 * FS];
};
__device__ __align__(1024) Scratch g_s;
#define STAMP(i) do { } while (0)

struct Maps {
  CUtensorMap wmod, x, wqkv128, wqkv64, wqkv32, wmod2, wo, oLd, oSt, x1Ld, x1St, w1a, w1b, w2, out, xOwn;
};

__device__ __forceinline__ uint32_t smem_u32(const void* p) { return (uint32_t)__cvta_generic_to_shared(p); }
__device__ __forceinline__ void mbar_init(uint32_t bar, uint32_t cnt) { asm volatile("mbarrier.init.shared::cta.b64 [%0], %1;" :: "r"(bar), "r"(cnt) : "memory"); }
__device__ __forceinline__ void mbar_expect(uint32_t bar, uint32_t bytes) { asm volatile("mbarrier.arrive.expect_tx.shared::cta.b64 _, [%0], %1;" :: "r"(bar), "r"(bytes) : "memory"); }
__device__ __forceinline__ void mbar_arrive(uint32_t bar) { asm volatile("mbarrier.arrive.shared::cta.b64 _, [%0];" :: "r"(bar) : "memory"); }
__device__ __forceinline__ uint32_t dep_on(uint32_t addr, uint32_t v) {
  uint32_t r;
  asm volatile("min.u32 %0, %1, %2;" : "=r"(r) : "r"(addr), "r"(v | 0x80000000u));
  return r;
}
__device__ __forceinline__ uint32_t mapa(uint32_t addr, uint32_t cta) { uint32_t r; asm volatile("mapa.shared::cluster.u32 %0, %1, %2;" : "=r"(r) : "r"(addr), "r"(cta)); return r; }
__device__ __forceinline__ void mbar_arrive_cluster(uint32_t raddr) { asm volatile("mbarrier.arrive.shared::cluster.b64 _, [%0];" :: "r"(raddr) : "memory"); }
__device__ __forceinline__ void mbar_wait(uint32_t bar, uint32_t parity) {
  asm volatile("{ .reg .pred p; .reg .u32 n; mov.u32 n, 0;\n"
               "W0: mbarrier.try_wait.parity.shared::cta.b64 p, [%0], %1;\n"
               "@p bra W1; add.u32 n, n, 1; setp.lt.u32 p, n, 262144; @p bra W0;\n"
               "W1: }" :: "r"(bar), "r"(parity) : "memory");
}
__device__ __forceinline__ uint32_t mbar_test(uint32_t bar, uint32_t parity) {
  uint32_t ok;
  asm volatile("{ .reg .pred p; mbarrier.test_wait.parity.shared::cta.b64 p, [%1], %2; selp.u32 %0, 1, 0, p; }" : "=r"(ok) : "r"(bar), "r"(parity) : "memory");
  return ok;
}
__device__ __forceinline__ void mbar_wait_cluster(uint32_t bar, uint32_t parity) {
  asm volatile("{ .reg .pred p; .reg .u32 n; mov.u32 n, 0;\n"
               "W0: mbarrier.try_wait.parity.acquire.cluster.shared::cta.b64 p, [%0], %1;\n"
               "@p bra W1; add.u32 n, n, 1; setp.lt.u32 p, n, 262144; @p bra W0;\n"
               "W1: }" :: "r"(bar), "r"(parity) : "memory");
}
__device__ __forceinline__ void st_async4(uint32_t dst, const uint32_t* v, uint32_t bar) {
  asm volatile("st.async.shared::cluster.mbarrier::complete_tx::bytes.v4.b32 [%0], {%1,%2,%3,%4}, [%5];"
               :: "r"(dst), "r"(v[0]), "r"(v[1]), "r"(v[2]), "r"(v[3]), "r"(bar) : "memory"); }
__device__ __forceinline__ void tma2d(uint32_t dst, const CUtensorMap* m, int c0, int c1, uint32_t bar) {
  asm volatile("cp.async.bulk.tensor.2d.shared::cluster.global.mbarrier::complete_tx::bytes [%0], [%1, {%3, %4}], [%2];" :: "r"(dst), "l"(m), "r"(bar), "r"(c0), "r"(c1) : "memory"); }
__device__ __forceinline__ void tma2d_mc(uint32_t dst, const CUtensorMap* m, int c0, int c1, uint32_t bar) {
  asm volatile("cp.async.bulk.tensor.2d.shared::cluster.global.mbarrier::complete_tx::bytes.multicast::cluster [%0], [%1, {%3, %4}], [%2], %5;"
               :: "r"(dst), "l"(m), "r"(bar), "r"(c0), "r"(c1), "h"((uint16_t)3) : "memory"); }
__device__ __forceinline__ void bulk_load_mc(uint32_t dst, const void* src, uint32_t bytes, uint32_t bar) {
  asm volatile("cp.async.bulk.shared::cluster.global.mbarrier::complete_tx::bytes.multicast::cluster [%0], [%1], %2, [%3], %4;"
               :: "r"(dst), "l"(src), "r"(bytes), "r"(bar), "h"((uint16_t)3) : "memory"); }
__device__ __forceinline__ void tma3d(uint32_t dst, const CUtensorMap* m, int c0, int c1, int c2, uint32_t bar) {
  asm volatile("cp.async.bulk.tensor.3d.shared::cluster.global.mbarrier::complete_tx::bytes [%0], [%1, {%3, %4, %5}], [%2];" :: "r"(dst), "l"(m), "r"(bar), "r"(c0), "r"(c1), "r"(c2) : "memory"); }
__device__ __forceinline__ void tma4d(uint32_t dst, const CUtensorMap* m, int c0, int c1, int c2, int c3, uint32_t bar) {
  asm volatile("cp.async.bulk.tensor.4d.shared::cluster.global.mbarrier::complete_tx::bytes [%0], [%1, {%3, %4, %5, %6}], [%2];" :: "r"(dst), "l"(m), "r"(bar), "r"(c0), "r"(c1), "r"(c2), "r"(c3) : "memory"); }
__device__ __forceinline__ void tma2d_store(const CUtensorMap* m, int c0, int c1, uint32_t src) {
  asm volatile("cp.async.bulk.tensor.2d.global.shared::cta.bulk_group [%0, {%2, %3}], [%1];" :: "l"(m), "r"(src), "r"(c0), "r"(c1) : "memory"); }
__device__ __forceinline__ void bulk_load(uint32_t dst, const void* src, uint32_t bytes, uint32_t bar) {
  asm volatile("cp.async.bulk.shared::cluster.global.mbarrier::complete_tx::bytes [%0], [%1], %2, [%3];" :: "r"(dst), "l"(src), "r"(bytes), "r"(bar) : "memory"); }
__device__ __forceinline__ void bulk_store(void* dst, uint32_t src, uint32_t bytes) {
  asm volatile("cp.async.bulk.global.shared::cta.bulk_group [%0], [%1], %2;" :: "l"(dst), "r"(src), "r"(bytes) : "memory"); }
__device__ __forceinline__ void bulk_commit() { asm volatile("cp.async.bulk.commit_group;" ::: "memory"); }
template <int N> __device__ __forceinline__ void bulk_wait() { asm volatile("cp.async.bulk.wait_group %0;" :: "n"(N) : "memory"); }
__device__ __forceinline__ void l2_prefetch(const void* p, uint32_t bytes) { asm volatile("cp.async.bulk.prefetch.L2.global [%0], %1;" :: "l"(p), "r"(bytes) : "memory"); }
__device__ __forceinline__ void fence_async_smem() { asm volatile("fence.proxy.async.shared::cta;" ::: "memory"); }
__device__ __forceinline__ void fence_async_global() { asm volatile("fence.proxy.async.global;" ::: "memory"); }
__device__ __forceinline__ void cons_sync() { asm volatile("bar.sync 1, 256;" ::: "memory"); }
__device__ __forceinline__ uint32_t ld_relaxed(const uint32_t* p) { uint32_t v; asm volatile("ld.relaxed.gpu.global.u32 %0, [%1];" : "=r"(v) : "l"(p) : "memory"); return v; }
__device__ __forceinline__ uint4 ld_relaxed4(const uint32_t* p) { uint4 v; asm volatile("ld.relaxed.gpu.global.v4.u32 {%0,%1,%2,%3}, [%4];" : "=r"(v.x), "=r"(v.y), "=r"(v.z), "=r"(v.w) : "l"(p) : "memory"); return v; }
__device__ __forceinline__ void st_relaxed(uint32_t* p, uint32_t v) { asm volatile("st.relaxed.gpu.global.u32 [%0], %1;" :: "l"(p), "r"(v) : "memory"); }
__device__ __forceinline__ void red_add(uint32_t* p, uint32_t v) { asm volatile("red.relaxed.gpu.global.add.u32 [%0], %1;" :: "l"(p), "r"(v) : "memory"); }
#define NSEND 6
#define PFS 4
#define BGATE 3
#define REL 7
__device__ __forceinline__ void fence_rel(int bit) { if (REL & bit) asm volatile("fence.release.gpu;" ::: "memory"); }
__device__ __forceinline__ void poll_ge(const uint32_t* p, uint32_t target) {
  uint32_t v; int n = 0;
  do {
    v = ld_relaxed(p);
    if (++n > (1 << 16)) break;
  } while ((int32_t)(v - target) < 0);
  asm volatile("fence.acquire.gpu;" ::: "memory");
}
__device__ __forceinline__ uint4 poll_tag4(const uint32_t* p, uint32_t tag) {
  uint4 v; int n = 0;
  do {
    v = ld_relaxed4(p);
    if (++n > (1 << 16)) break;
  } while ((((v.x ^ tag) | (v.y ^ tag) | (v.z ^ tag) | (v.w ^ tag)) & 0xFFFFu) != 0);
  return v;
}
__device__ __forceinline__ void ldsm4(uint32_t (&r)[4], uint32_t addr) {
  asm volatile("ldmatrix.sync.aligned.m8n8.x4.shared.b16 {%0,%1,%2,%3}, [%4];" : "=r"(r[0]), "=r"(r[1]), "=r"(r[2]), "=r"(r[3]) : "r"(addr) : "memory"); }
__device__ __forceinline__ void ldsm2(uint32_t& r0, uint32_t& r1, uint32_t addr) {
  asm volatile("ldmatrix.sync.aligned.m8n8.x2.shared.b16 {%0,%1}, [%2];" : "=r"(r0), "=r"(r1) : "r"(addr) : "memory"); }
__device__ __forceinline__ void ldsm4t(uint32_t (&r)[4], uint32_t addr) {
  asm volatile("ldmatrix.sync.aligned.m8n8.x4.trans.shared.b16 {%0,%1,%2,%3}, [%4];" : "=r"(r[0]), "=r"(r[1]), "=r"(r[2]), "=r"(r[3]) : "r"(addr) : "memory"); }
__device__ __forceinline__ void ldsm2t(uint32_t& r0, uint32_t& r1, uint32_t addr) {
  asm volatile("ldmatrix.sync.aligned.m8n8.x2.trans.shared.b16 {%0,%1}, [%2];" : "=r"(r0), "=r"(r1) : "r"(addr) : "memory"); }
__device__ __forceinline__ void stsm4(uint32_t addr, uint32_t r0, uint32_t r1, uint32_t r2, uint32_t r3) {
  asm volatile("stmatrix.sync.aligned.m8n8.x4.shared.b16 [%0], {%1,%2,%3,%4};" :: "r"(addr), "r"(r0), "r"(r1), "r"(r2), "r"(r3) : "memory"); }
__device__ __forceinline__ void sts32(uint32_t addr, uint32_t v) { asm volatile("st.shared.b32 [%0], %1;" :: "r"(addr), "r"(v) : "memory"); }
__device__ __forceinline__ void stsf(uint32_t addr, float v) { asm volatile("st.shared.f32 [%0], %1;" :: "r"(addr), "f"(v) : "memory"); }
__device__ __forceinline__ void sts128(uint32_t addr, uint32_t a, uint32_t b, uint32_t c, uint32_t d) { asm volatile("st.shared.v4.b32 [%0], {%1,%2,%3,%4};" :: "r"(addr), "r"(a), "r"(b), "r"(c), "r"(d) : "memory"); }
__device__ __forceinline__ uint32_t lds32(uint32_t addr) { uint32_t v; asm volatile("ld.shared.b32 %0, [%1];" : "=r"(v) : "r"(addr) : "memory"); return v; }
__device__ __forceinline__ float ldsf(uint32_t addr) { float v; asm volatile("ld.shared.f32 %0, [%1];" : "=f"(v) : "r"(addr) : "memory"); return v; }
__device__ __forceinline__ float2 ldsf2(uint32_t addr) { float2 v; asm volatile("ld.shared.v2.f32 {%0,%1}, [%2];" : "=f"(v.x), "=f"(v.y) : "r"(addr) : "memory"); return v; }
__device__ __forceinline__ float4 ldsf4(uint32_t addr) { float4 v; asm volatile("ld.shared.v4.f32 {%0,%1,%2,%3}, [%4];" : "=f"(v.x), "=f"(v.y), "=f"(v.z), "=f"(v.w) : "r"(addr) : "memory"); return v; }
__device__ __forceinline__ uint4 lds128(uint32_t addr) { uint4 v; asm volatile("ld.shared.v4.b32 {%0,%1,%2,%3}, [%4];" : "=r"(v.x), "=r"(v.y), "=r"(v.z), "=r"(v.w) : "r"(addr) : "memory"); return v; }
__device__ __forceinline__ uint32_t pack2(float lo, float hi) { uint32_t r; asm("cvt.rn.bf16x2.f32 %0, %1, %2;" : "=r"(r) : "f"(hi), "f"(lo)); return r; }
__device__ __forceinline__ float blo(uint32_t v) { return __uint_as_float(v << 16); }
__device__ __forceinline__ float bhi(uint32_t v) { return __uint_as_float(v & 0xFFFF0000u); }
__device__ __forceinline__ float ex2(float x) { float y; asm("ex2.approx.ftz.f32 %0, %1;" : "=f"(y) : "f"(x)); return y; }
__device__ __forceinline__ float tanh_fast(float x) { float y; asm("tanh.approx.f32 %0, %1;" : "=f"(y) : "f"(x)); return y; }
__device__ __forceinline__ float round_bf16(float x) { return __bfloat162float(__float2bfloat16_rn(x)); }
__device__ __forceinline__ float rcp_fast(float x) { float y; asm("rcp.approx.ftz.f32 %0, %1;" : "=f"(y) : "f"(x)); return y; }
__device__ __forceinline__ float silu_f(float c) { return c * rcp_fast(1.f + ex2(-1.4426950408889634f * c)); }
__device__ __forceinline__ float silu_bf16(float c) { return round_bf16(c * rcp_fast(1.f + ex2(-1.4426950408889634f * c))); }
__device__ __forceinline__ void mma16(float (&d)[4], const uint32_t (&a)[4], uint32_t b0, uint32_t b1) {
  asm("mma.sync.aligned.m16n8k16.row.col.f32.bf16.bf16.f32 {%0,%1,%2,%3}, {%4,%5,%6,%7}, {%8,%9}, {%0,%1,%2,%3};"
      : "+f"(d[0]), "+f"(d[1]), "+f"(d[2]), "+f"(d[3]) : "r"(a[0]), "r"(a[1]), "r"(a[2]), "r"(a[3]), "r"(b0), "r"(b1)); }
__device__ __forceinline__ void mma8_init(float (&d)[4], uint32_t a0, uint32_t a1, uint32_t b0, float c) {
  asm("mma.sync.aligned.m16n8k8.row.col.f32.bf16.bf16.f32 {%0,%1,%2,%3}, {%4,%5}, {%6}, {%7,%7,%7,%7};"
      : "=f"(d[0]), "=f"(d[1]), "=f"(d[2]), "=f"(d[3]) : "r"(a0), "r"(a1), "r"(b0), "f"(c)); }
__device__ __forceinline__ void wg_fence() { asm volatile("wgmma.fence.sync.aligned;" ::: "memory"); }
__device__ __forceinline__ void wg_commit() { asm volatile("wgmma.commit_group.sync.aligned;" ::: "memory"); }
template <int N> __device__ __forceinline__ void wg_wait() { asm volatile("wgmma.wait_group.sync.aligned %0;" :: "n"(N) : "memory"); }
template <int M> __device__ __forceinline__ void fence_regs(float (&d)[M]) {
#pragma unroll
  for (int i = 0; i < M; i++) asm volatile("" : "+f"(d[i]) :: "memory");
}
template <int M> __device__ __forceinline__ void fence_regs(uint32_t (&d)[M]) {
#pragma unroll
  for (int i = 0; i < M; i++) asm volatile("" : "+r"(d[i]) :: "memory");
}
__device__ __forceinline__ uint64_t mkdesc(uint32_t addr, uint32_t lbo, uint32_t sbo, uint32_t sw) {
  uint32_t lo = ((addr & 0x3FFFFu) >> 4) | ((lbo >> 4) << 16);
  uint32_t hi = (sbo >> 4) | (sw << 30);
  return ((uint64_t)hi << 32) | lo;
}

__device__ __forceinline__ void wgmma_rs_n192(float (&d)[96], const uint32_t* a, uint64_t descB, int scaleD) {
  asm volatile("{ .reg .pred p; setp.ne.b32 p, %101, 0; wgmma.mma_async.sync.aligned.m64n192k16.f32.bf16.bf16 {%0, %1, %2, %3, %4, %5, %6, %7, %8, %9, %10, %11, %12, %13, %14, %15, %16, %17, %18, %19, %20, %21, %22, %23, %24, %25, %26, %27, %28, %29, %30, %31, %32, %33, %34, %35, %36, %37, %38, %39, %40, %41, %42, %43, %44, %45, %46, %47, %48, %49, %50, %51, %52, %53, %54, %55, %56, %57, %58, %59, %60, %61, %62, %63, %64, %65, %66, %67, %68, %69, %70, %71, %72, %73, %74, %75, %76, %77, %78, %79, %80, %81, %82, %83, %84, %85, %86, %87, %88, %89, %90, %91, %92, %93, %94, %95}, {%96, %97, %98, %99}, %100, p, 1, 1, 1; }"
    : "+f"(d[0]), "+f"(d[1]), "+f"(d[2]), "+f"(d[3]), "+f"(d[4]), "+f"(d[5]), "+f"(d[6]), "+f"(d[7]), "+f"(d[8]), "+f"(d[9]), "+f"(d[10]), "+f"(d[11]), "+f"(d[12]), "+f"(d[13]), "+f"(d[14]), "+f"(d[15]), "+f"(d[16]), "+f"(d[17]), "+f"(d[18]), "+f"(d[19]), "+f"(d[20]), "+f"(d[21]), "+f"(d[22]), "+f"(d[23]), "+f"(d[24]), "+f"(d[25]), "+f"(d[26]), "+f"(d[27]), "+f"(d[28]), "+f"(d[29]), "+f"(d[30]), "+f"(d[31]), "+f"(d[32]), "+f"(d[33]), "+f"(d[34]), "+f"(d[35]), "+f"(d[36]), "+f"(d[37]), "+f"(d[38]), "+f"(d[39]), "+f"(d[40]), "+f"(d[41]), "+f"(d[42]), "+f"(d[43]), "+f"(d[44]), "+f"(d[45]), "+f"(d[46]), "+f"(d[47]), "+f"(d[48]), "+f"(d[49]), "+f"(d[50]), "+f"(d[51]), "+f"(d[52]), "+f"(d[53]), "+f"(d[54]), "+f"(d[55]), "+f"(d[56]), "+f"(d[57]), "+f"(d[58]), "+f"(d[59]), "+f"(d[60]), "+f"(d[61]), "+f"(d[62]), "+f"(d[63]), "+f"(d[64]), "+f"(d[65]), "+f"(d[66]), "+f"(d[67]), "+f"(d[68]), "+f"(d[69]), "+f"(d[70]), "+f"(d[71]), "+f"(d[72]), "+f"(d[73]), "+f"(d[74]), "+f"(d[75]), "+f"(d[76]), "+f"(d[77]), "+f"(d[78]), "+f"(d[79]), "+f"(d[80]), "+f"(d[81]), "+f"(d[82]), "+f"(d[83]), "+f"(d[84]), "+f"(d[85]), "+f"(d[86]), "+f"(d[87]), "+f"(d[88]), "+f"(d[89]), "+f"(d[90]), "+f"(d[91]), "+f"(d[92]), "+f"(d[93]), "+f"(d[94]), "+f"(d[95])
    : "r"(a[0]), "r"(a[1]), "r"(a[2]), "r"(a[3]), "l"(descB), "r"(scaleD));
}
__device__ __forceinline__ void wgmma_rs_n48(float (&d)[24], const uint32_t* a, uint64_t descB, int scaleD) {
  asm volatile("{ .reg .pred p; setp.ne.b32 p, %29, 0; wgmma.mma_async.sync.aligned.m64n48k16.f32.bf16.bf16 {%0, %1, %2, %3, %4, %5, %6, %7, %8, %9, %10, %11, %12, %13, %14, %15, %16, %17, %18, %19, %20, %21, %22, %23}, {%24, %25, %26, %27}, %28, p, 1, 1, 1; }"
    : "+f"(d[0]), "+f"(d[1]), "+f"(d[2]), "+f"(d[3]), "+f"(d[4]), "+f"(d[5]), "+f"(d[6]), "+f"(d[7]), "+f"(d[8]), "+f"(d[9]), "+f"(d[10]), "+f"(d[11]), "+f"(d[12]), "+f"(d[13]), "+f"(d[14]), "+f"(d[15]), "+f"(d[16]), "+f"(d[17]), "+f"(d[18]), "+f"(d[19]), "+f"(d[20]), "+f"(d[21]), "+f"(d[22]), "+f"(d[23])
    : "r"(a[0]), "r"(a[1]), "r"(a[2]), "r"(a[3]), "l"(descB), "r"(scaleD));
}
__device__ __forceinline__ void wgmma_rs_n32(float (&d)[16], const uint32_t* a, uint64_t descB, int scaleD) {
  asm volatile("{ .reg .pred p; setp.ne.b32 p, %21, 0; wgmma.mma_async.sync.aligned.m64n32k16.f32.bf16.bf16 {%0, %1, %2, %3, %4, %5, %6, %7, %8, %9, %10, %11, %12, %13, %14, %15}, {%16, %17, %18, %19}, %20, p, 1, 1, 1; }"
    : "+f"(d[0]), "+f"(d[1]), "+f"(d[2]), "+f"(d[3]), "+f"(d[4]), "+f"(d[5]), "+f"(d[6]), "+f"(d[7]), "+f"(d[8]), "+f"(d[9]), "+f"(d[10]), "+f"(d[11]), "+f"(d[12]), "+f"(d[13]), "+f"(d[14]), "+f"(d[15])
    : "r"(a[0]), "r"(a[1]), "r"(a[2]), "r"(a[3]), "l"(descB), "r"(scaleD));
}
__device__ __forceinline__ void wgmma_rs_n64(float (&d)[32], const uint32_t* a, uint64_t descB, int scaleD) {
  asm volatile("{ .reg .pred p; setp.ne.b32 p, %37, 0; wgmma.mma_async.sync.aligned.m64n64k16.f32.bf16.bf16 {%0, %1, %2, %3, %4, %5, %6, %7, %8, %9, %10, %11, %12, %13, %14, %15, %16, %17, %18, %19, %20, %21, %22, %23, %24, %25, %26, %27, %28, %29, %30, %31}, {%32, %33, %34, %35}, %36, p, 1, 1, 1; }"
    : "+f"(d[0]), "+f"(d[1]), "+f"(d[2]), "+f"(d[3]), "+f"(d[4]), "+f"(d[5]), "+f"(d[6]), "+f"(d[7]), "+f"(d[8]), "+f"(d[9]), "+f"(d[10]), "+f"(d[11]), "+f"(d[12]), "+f"(d[13]), "+f"(d[14]), "+f"(d[15]), "+f"(d[16]), "+f"(d[17]), "+f"(d[18]), "+f"(d[19]), "+f"(d[20]), "+f"(d[21]), "+f"(d[22]), "+f"(d[23]), "+f"(d[24]), "+f"(d[25]), "+f"(d[26]), "+f"(d[27]), "+f"(d[28]), "+f"(d[29]), "+f"(d[30]), "+f"(d[31])
    : "r"(a[0]), "r"(a[1]), "r"(a[2]), "r"(a[3]), "l"(descB), "r"(scaleD));
}
__device__ __forceinline__ void wgmma_ss_n80(float (&d)[40], uint64_t descA, uint64_t descB, int scaleD) {
  asm volatile("{ .reg .pred p; setp.ne.b32 p, %42, 0; wgmma.mma_async.sync.aligned.m64n80k16.f32.bf16.bf16 {%0, %1, %2, %3, %4, %5, %6, %7, %8, %9, %10, %11, %12, %13, %14, %15, %16, %17, %18, %19, %20, %21, %22, %23, %24, %25, %26, %27, %28, %29, %30, %31, %32, %33, %34, %35, %36, %37, %38, %39}, %40, %41, p, 1, 1, 0, 1; }"
    : "+f"(d[0]), "+f"(d[1]), "+f"(d[2]), "+f"(d[3]), "+f"(d[4]), "+f"(d[5]), "+f"(d[6]), "+f"(d[7]), "+f"(d[8]), "+f"(d[9]), "+f"(d[10]), "+f"(d[11]), "+f"(d[12]), "+f"(d[13]), "+f"(d[14]), "+f"(d[15]), "+f"(d[16]), "+f"(d[17]), "+f"(d[18]), "+f"(d[19]), "+f"(d[20]), "+f"(d[21]), "+f"(d[22]), "+f"(d[23]), "+f"(d[24]), "+f"(d[25]), "+f"(d[26]), "+f"(d[27]), "+f"(d[28]), "+f"(d[29]), "+f"(d[30]), "+f"(d[31]), "+f"(d[32]), "+f"(d[33]), "+f"(d[34]), "+f"(d[35]), "+f"(d[36]), "+f"(d[37]), "+f"(d[38]), "+f"(d[39])
    : "l"(descA), "l"(descB), "r"(scaleD));
}

template <int N2> struct W2nd;
template <> struct W2nd<48> { static __device__ __forceinline__ void go(float (&d)[24], const uint32_t* a, uint64_t b, int s) { wgmma_rs_n48(d, a, b, s); } };
template <> struct W2nd<32> { static __device__ __forceinline__ void go(float (&d)[16], const uint32_t* a, uint64_t b, int s) { wgmma_rs_n32(d, a, b, s); } };

struct Ids { int tid, warp, lane, wg, w4, q, gq, row0; };
__device__ __forceinline__ Ids fresh_ids() {
  Ids t;
  asm volatile("mov.u32 %0, %%tid.x;" : "=r"(t.tid));
  t.warp = t.tid >> 5; t.lane = t.tid & 31; t.wg = t.warp >> 2; t.w4 = t.warp & 3; t.q = t.lane & 3; t.gq = t.lane >> 2;
  t.row0 = 16 * t.warp + t.gq;
  return t;
}
#define IDS() const Ids id_ = fresh_ids(); const int tid = id_.tid, warp = id_.warp, lane = id_.lane, wg = id_.wg, w4 = id_.w4, q = id_.q, gq = id_.gq, row0 = id_.row0; \
  const bool stamp = (tid & 127) == 0; (void)tid; (void)warp; (void)lane; (void)wg; (void)w4; (void)q; (void)gq; (void)row0; (void)stamp;

struct RowC { uint32_t P0, Q0, R0, T0, P1, Q1, R1, T1; };
__device__ __forceinline__ uint32_t hfma2(uint32_t a, uint32_t b, uint32_t c) { uint32_t d; asm("fma.rn.bf16x2 %0, %1, %2, %3;" : "=r"(d) : "r"(a), "r"(b), "r"(c)); return d; }
__device__ __forceinline__ uint32_t hmul2(uint32_t a, uint32_t b) { uint32_t d; asm("mul.rn.bf16x2 %0, %1, %2;" : "=r"(d) : "r"(a), "r"(b)); return d; }
__device__ __forceinline__ uint32_t dup2(float v) { return pack2(v, v); }

__device__ __forceinline__ uint32_t tab_off(int c) { return (c >> 4) * 64 + ((c & 7) >> 1) * 16 + ((c >> 3) & 1) * 4 + (c & 1) * 2; }
__device__ __forceinline__ int x1_perm(int i, int keep0, int keep1) {
  int j = i + (i >= keep0 ? 1 : 0);
  j += (j >= keep1 ? 1 : 0);
  j = i == 8 ? keep0 : j;
  return i == 9 ? keep1 : j;
}

struct Raw { uint32_t x[4]; uint4 t; };
__device__ __forceinline__ void load_raw(Raw& r, uint32_t a, uint32_t tab) { ldsm4(r.x, a); r.t = lds128(tab); }
template <bool MLP>
__device__ __forceinline__ void xform(uint32_t* fr, const Raw& r, const RowC& rc) {
  uint32_t u0 = r.t.z, u1 = r.t.z, v0 = r.t.w, v1 = r.t.w;
  if (MLP) { u0 = hfma2(r.t.z, rc.R0, rc.T0); u1 = hfma2(r.t.z, rc.R1, rc.T1); v0 = hfma2(r.t.w, rc.R0, rc.T0); v1 = hfma2(r.t.w, rc.R1, rc.T1); }
  const uint32_t z0 = hfma2(r.x[0], rc.P0, rc.Q0), z1 = hfma2(r.x[1], rc.P1, rc.Q1), z2 = hfma2(r.x[2], rc.P0, rc.Q0), z3 = hfma2(r.x[3], rc.P1, rc.Q1);
  fr[0] = hfma2(z0, r.t.x, u0); fr[1] = hfma2(z1, r.t.x, u1); fr[2] = hfma2(z2, r.t.y, v0); fr[3] = hfma2(z3, r.t.y, v1);
}

template <int N2, bool MLP>
__device__ __forceinline__ void gemm_norm(float (&acc1)[96], float (&acc2)[N2 / 2], uint32_t sb, int warp, int lane,
                                          const RowC& rc, int keep0, int keep1, bool two) {
  constexpr int GS0 = MLP ? 20 : 0;
  const uint32_t bars = sb + OFF_BAR;
  uint32_t arow = sb + (uint32_t)(16 * warp + (lane & 15)) * 128u;
  const uint32_t c0 = ((lane >> 4) ^ (lane & 7)) << 4;
  const uint32_t tabq = sb + OFF_AB + (lane & 3) * 16;
  const uint64_t dA = two ? mkdesc(sb, 2048, 512, 2) : mkdesc(sb, 4096, 1024, 1);
  const uint32_t KA = two ? 64 : 128;
  const uint64_t dB = MLP ? mkdesc(sb + 12288, 2048, 512, 2) : mkdesc(sb + 12288, 1024, 256, 3);
  constexpr uint32_t KB = MLP ? 64 : 32;
  uint32_t fr[4][4];
  Raw raw[2];
  uint32_t tab = tabq + (MLP ? x1_perm(0, keep0, keep1) : 0) * 256;
  if (MLP) mbar_wait(bars + 8 * (B_TILE + 0), 0);
  load_raw(raw[0], arow + c0, tab); load_raw(raw[1], arow + (c0 ^ 32), tab + 64);
  xform<MLP>(fr[0], raw[0], rc); xform<MLP>(fr[1], raw[1], rc);
  load_raw(raw[0], arow + (c0 ^ 64), tab + 128); load_raw(raw[1], arow + (c0 ^ 96), tab + 192);
  if (MLP) { fence_regs(acc1); fence_regs(acc2); }
  uint32_t ok = 0;
  uint64_t da = dA + (OFF_RING >> 4), db = dB + (OFF_RING >> 4);
  uint32_t tw[5] = {MLP ? 0x60CDBEAFu : 0xA0CDBEAFu, MLP ? 0xAF00A070u : 0x10BEAF00u, MLP ? 0x20CD10BEu : 0x0020A0CDu, MLP ? 0x4000A030u : 0x10BE30AFu, MLP ? 0x005010AFu : 0x0020A040u};
#pragma unroll 1
  for (int i = 0; i < 10; i++) {
#pragma unroll
    for (int u = 0; u < 4; u++) {
      const int s = 2 * i + (u >> 1), G = GS0 + s;
      if (!(u & 1)) {
        if (!ok) {
          mbar_wait(bars + 8 * (B_RFULL + (G & 7)), (G >> 3) & 1);
          if (MLP && u == 0) mbar_wait(bars + 8 * (B_TILE + (i < 9 ? i + 1 : 9)), 0);
        }
      }
      fence_regs(fr[u]);
      wg_fence();
      W2nd<N2>::go(acc2, fr[u], db, MLP || u != 0 || i != 0);
      wgmma_rs_n192(acc1, fr[u], da, MLP || u != 0 || i != 0);
      wg_commit();
      if (u & 1) {
        const uint32_t so = ((tw[0] >> (4 * (u - 1))) & 0xFFu) << 6;
        da = dA + so; db = dB + so;
        if (u == 3) {
#pragma unroll
          for (int e = 0; e < 4; e++) tw[e] = __funnelshift_r(tw[e], tw[e + 1], 16);
          tw[4] >>= 16;
        }
      } else { da += KA; db += KB; }
      xform<MLP>(fr[(u + 2) & 3], raw[u & 1], rc);
      if (u == 0) {
        arow += 16384;
        tab = tabq + (MLP ? x1_perm(i + 1, keep0, keep1) : i + 1) * 256;
      }
      load_raw(raw[u & 1], arow + (c0 ^ (32 * u)), tab + 64 * u);
      if (u & 1) {
        ok = mbar_test(bars + 8 * (B_RFULL + ((G + 1) & 7)), ((G + 1) >> 3) & 1);
        if (MLP && u == 3) ok &= mbar_test(bars + 8 * (B_TILE + (i < 8 ? i + 2 : 9)), 0);
      }
      fence_regs(fr[(u + 2) & 3]);
      __syncwarp();
      wg_wait<1>();
      fence_regs(fr[(u + 3) & 3]);
      if (!(u & 1) && s != 0 && lane == 0) mbar_arrive(bars + 8 * (B_REMPTY + ((G - 1) & 7)));
    }
  }
  wg_wait<0>();
  fence_regs(acc1);
  fence_regs(acc2);
  if (lane == 0) mbar_arrive(bars + 8 * (B_REMPTY + ((GS0 + 19) & 7)));
}

__device__ __forceinline__ void attn_head(uint32_t (&qo)[24], uint32_t wb  , int odd,
                                          int lane, int jmin, const uint32_t (&msk)[4], bool signal) {
  const uint32_t a16[4] = {qo[0], qo[1], qo[2], qo[3]};
  const uint32_t a80 = qo[4], a81 = qo[5];
  const uint32_t ka = wb + ((lane & 7) + 8 * (lane >> 4)) * 80 + (3 * odd + ((lane >> 3) & 1)) * 16;
  const uint32_t k8a = wb + lane * 80 + 32;
  const uint32_t va = wb + ((lane & 7) + 8 * ((lane >> 3) & 1)) * 80 + (2 - 2 * odd + (lane >> 4)) * 16;
  const uint32_t v2a = wb + lane * 80 + (4 - 2 * odd) * 16;
  const uint32_t dg = (lane >> 4) * 1280;
  const float NINF = __int_as_float(0xff800000);

  float s[17][2][4];
  {
    uint32_t k80, k81, kb[4];
    ldsm2(k80, k81, k8a - dg + 16 * 1280);
    ldsm4(kb, ka + 16 * 1280);
    mma8_init(s[16][0], a80, a81, k80, 0.f); mma16(s[16][0], a16, kb[0], kb[1]);
    mma8_init(s[16][1], a80, a81, k81, 0.f); mma16(s[16][1], a16, kb[2], kb[3]);
  }
#pragma unroll
  for (int jp = 0; jp < 8; jp++) {
    uint32_t k8[4];
    ldsm4(k8, k8a + jp * 2560);
#pragma unroll
    for (int u = 0; u < 2; u++) {
      const int j = 2 * jp + u;
      uint32_t kb[4];
      ldsm4(kb, ka + j * 1280);
      mma8_init(s[j][0], a80, a81, k8[2 * u], 0.f); mma8_init(s[j][1], a80, a81, k8[2 * u + 1], 0.f);
      mma16(s[j][0], a16, kb[0], kb[1]); mma16(s[j][1], a16, kb[2], kb[3]);
    }
  }
#pragma unroll
  for (int i = 0; i < 18; i++) qo[i] = qo[i + 6];
  const float bias0 = jmin > 0 ? NINF : 0.f;
#pragma unroll
  for (int nb = 0; nb < 2; nb++)
#pragma unroll
    for (int e = 0; e < 4; e++) {
      const uint32_t m = msk[2 * nb + (e >> 1)];
      const bool up = (e & 1) ? (m >> 16) != 0 : (m & 0xFFFFu) != 0;
      s[0][nb][e] = up ? s[0][nb][e] + bias0 : s[16][nb][e];
    }
  int i0m = __float_as_int(s[0][0][0]), i1m = __float_as_int(s[0][0][2]);
  i0m = __vimax3_s32(i0m, __float_as_int(s[0][0][1]), __float_as_int(s[0][1][0])); i1m = __vimax3_s32(i1m, __float_as_int(s[0][0][3]), __float_as_int(s[0][1][2]));
  int j0m = __float_as_int(s[0][1][1]), j1m = __float_as_int(s[0][1][3]);
#pragma unroll
  for (int j = 1; j < 16; j++) {
    i0m = __vimax3_s32(i0m, __float_as_int(s[j][0][0]), __float_as_int(s[j][0][1])); j0m = __vimax3_s32(j0m, __float_as_int(s[j][1][0]), __float_as_int(s[j][1][1]));
    i1m = __vimax3_s32(i1m, __float_as_int(s[j][0][2]), __float_as_int(s[j][0][3])); j1m = __vimax3_s32(j1m, __float_as_int(s[j][1][2]), __float_as_int(s[j][1][3]));
  }
  i0m = max(i0m, j0m); i1m = max(i1m, j1m);
  i0m = max(i0m, __shfl_xor_sync(0xffffffffu, i0m, 1)); i1m = max(i1m, __shfl_xor_sync(0xffffffffu, i1m, 1));
  i0m = max(i0m, __shfl_xor_sync(0xffffffffu, i0m, 2)); i1m = max(i1m, __shfl_xor_sync(0xffffffffu, i1m, 2));
  float m0 = __int_as_float(i0m), m1 = __int_as_float(i1m);
  if (__any_sync(0xffffffffu, min(i0m, i1m) <= 0)) {
    m0 = NINF; m1 = NINF;
#pragma unroll
    for (int j = 0; j < 16; j++) {
      const float bj = (j == 0 || j >= jmin) ? 0.f : NINF;
      m0 = fmaxf(m0, fmaxf(fmaxf(s[j][0][0], s[j][0][1]), fmaxf(s[j][1][0], s[j][1][1])) + bj);
      m1 = fmaxf(m1, fmaxf(fmaxf(s[j][0][2], s[j][0][3]), fmaxf(s[j][1][2], s[j][1][3])) + bj);
    }
    m0 = fmaxf(m0, __shfl_xor_sync(0xffffffffu, m0, 1)); m0 = fmaxf(m0, __shfl_xor_sync(0xffffffffu, m0, 2));
    m1 = fmaxf(m1, __shfl_xor_sync(0xffffffffu, m1, 1)); m1 = fmaxf(m1, __shfl_xor_sync(0xffffffffu, m1, 2));
  }
  if (signal) asm volatile("bar.arrive 2, 256;" ::: "memory");
  constexpr float CS = 0.22360679774997896f * 1.4426950408889634f;
  const float n0 = -m0 * CS, n1 = -m1 * CS;
  float o[4][4];
#pragma unroll
  for (int i = 0; i < 4; i++) { o[i][0] = 0.f; o[i][1] = 0.f; o[i][2] = 0.f; o[i][3] = 0.f; }
#pragma unroll
  for (int jp = 0; jp < 8; jp++) {
    uint32_t v2[4];
    ldsm4t(v2, v2a + jp * 2560);
#pragma unroll
    for (int u = 0; u < 2; u++) {
      const int j = 2 * jp + u;
      float pv[2][4];
      const float b0 = (j == 0 || j >= jmin) ? n0 : NINF, b1 = (j == 0 || j >= jmin) ? n1 : NINF;
#pragma unroll
      for (int nb = 0; nb < 2; nb++) {
        pv[nb][0] = ex2(fmaf(s[j][nb][0], CS, b0)); pv[nb][1] = ex2(fmaf(s[j][nb][1], CS, b0));
        pv[nb][2] = ex2(fmaf(s[j][nb][2], CS, b1)); pv[nb][3] = ex2(fmaf(s[j][nb][3], CS, b1));
      }
      uint32_t pa[4] = {pack2(pv[0][0], pv[0][1]), pack2(pv[0][2], pv[0][3]), pack2(pv[1][0], pv[1][1]), pack2(pv[1][2], pv[1][3])};
      uint32_t vb[4];
      ldsm4t(vb, va + j * 1280);
      mma16(o[3], pa, 0x3F803F80u, 0x3F803F80u);
      if (j == 0) {
        uint32_t pd[4] = {pa[0] & ~msk[0], pa[1] & ~msk[1], pa[2] & ~msk[2], pa[3] & ~msk[3]};
        uint32_t vd[4], vd0, vd1;
        ldsm4t(vd, va + 16 * 1280);
        ldsm2t(vd0, vd1, v2a - dg + 16 * 1280);
        mma16(o[0], pd, vd[0], vd[1]); mma16(o[1], pd, vd[2], vd[3]); mma16(o[2], pd, vd0, vd1);
        pa[0] &= msk[0]; pa[1] &= msk[1]; pa[2] &= msk[2]; pa[3] &= msk[3];
      }
      mma16(o[0], pa, vb[0], vb[1]); mma16(o[1], pa, vb[2], vb[3]); mma16(o[2], pa, v2[2 * u], v2[2 * u + 1]);
    }
  }
  const float i0 = rcp_fast(o[3][0]), i1 = rcp_fast(o[3][2]);
#pragma unroll
  for (int i = 0; i < 3; i++) {
    qo[18 + 2 * i] = pack2(o[i][0] * i0, o[i][1] * i0);
    qo[18 + 2 * i + 1] = pack2(o[i][2] * i1, o[i][3] * i1);
  }
}

__device__ __forceinline__ float gelu_tanh(float v) {
  const float u = v * fmaf(v * v, 0.7978845608028654f * 0.044715f, 0.7978845608028654f);
  const float h = 0.5f * v;
  return fmaf(h, tanh_fast(u), h);
}

struct Role { int p, rb, hf, g, cta, keep0, keep1; };
__device__ __forceinline__ Role read_role(uint32_t sb) {
  Role r;
  const uint32_t v = __shfl_sync(0xffffffffu, lds32(sb + OFF_ROLE), 0);
  r.hf = blockIdx.x & 1; r.p = (v >> 4) & 3; r.rb = v & 15; r.g = 2 * r.p + r.hf; r.cta = 8 * r.rb + r.g;
  r.keep0 = 5 * r.hf + r.p; r.keep1 = 5 * r.hf + 4;
  return r;
}
#define ROLE() const Role ro_ = read_role(sb); const int p = ro_.p, rb = ro_.rb, g = ro_.g, cta = ro_.cta, keep0 = ro_.keep0, keep1 = ro_.keep1; \
  (void)p; (void)rb; (void)g; (void)cta; (void)keep0; (void)keep1;

__device__ __forceinline__ void wait_release(uint32_t bars, int G) { mbar_wait(bars + 8 * (B_REMPTY + (G & 7)), (G >> 3) & 1); }

__device__ __forceinline__ void w1_stream(const Maps& maps, uint32_t sb, int odd, int p, int hf, int keep0, int keep1, int rb) {
  const uint32_t bars = sb + OFF_BAR;
  const int atom0 = 7 * p + 4 * hf, colb = 448 * p + 192 + 32 * hf;
#pragma unroll 1
  for (int s = odd; s < 20; s += odd ? (s == 3 || s == 4 ? 1 : 2) : (s == 2 ? 4 : 2)) {
    const int G = 20 + s, dep = nib(MD_LO, MD_HI, s);
    if (dep) wait_release(bars, 19 + dep);
    const uint32_t dst = sb + unit_off(nib(MU_LO, MU_HI, s)), bar = bars + 8 * (B_RFULL + (G & 7));
    const int k0 = 64 * x1_perm(s >> 1, keep0, keep1) + 32 * (s & 1);
    mbar_expect(bar, W1_STAGE);
    tma3d(dst, &maps.w1a, 0, k0, atom0, bar);
    tma2d(dst + 12288, &maps.w1b, colb, k0, bar);
    if ((s & ~5) == 8) {
      const int i = s < 12 ? s : s - 6;
      fence_async_global();
      mbar_expect(bars + 8 * (B_TILE + i), 16384);
      tma2d(sb + i * 16384, &maps.x1Ld, 64 * x1_perm(i, keep0, keep1), 128 * rb, bars + 8 * (B_TILE + i));
    }
  }
}

__device__ __forceinline__ void publish_partials(Scratch* gs, uint32_t sb, int first, int rh, int p, uint32_t epoch) {
  const uint32_t bars = sb + OFF_BAR;
#pragma unroll 1
  for (int c = first; c < 4; c += 2) {
    mbar_wait(bars + 8 * (B_PSTG + c), 0);
    const int dest = (p + c) & 3;
    uint8_t* dst = c == 0 ? gs->part4 + (size_t)(rh * 4 + p) * 16384 : gs->part + (size_t)((rh * 4 + dest) * 3 + (c - 1)) * 16384;
    bulk_store(dst, sb + OFF_PSTG + (c & 1) * 16384, 16384);
    bulk_commit(); bulk_wait<0>();
    if (c < 2) mbar_arrive(bars + 8 * (B_PFREE + c));
    fence_rel(4);
    if (c == 0) red_add(&gs->p4flag[rh * FS], 1);
    else st_relaxed(&gs->pflag[((rh * 4 + dest) * 4 + (c - 1)) * FS / 4], epoch);
  }
}

__device__ __forceinline__ void stat_put(uint32_t* dst, float a, float b, float c, uint32_t tag) {
  asm volatile("{ .reg .b64 lo, hi; mov.b64 lo, {%1,%2}; mov.b64 hi, {%3,%4}; st.relaxed.gpu.global.v2.b64 [%0], {lo, hi}; }"
               :: "l"(dst), "r"((__float_as_uint(a) & ~7u) | (tag & 7u)), "r"((__float_as_uint(b) & ~7u) | ((tag >> 3) & 7u)), "r"(__float_as_uint(c)), "r"(tag) : "memory");
}

__global__ void __cluster_dims__(2, 1, 1) __launch_bounds__(384, 1)
fused_block_kernel(const __nv_bfloat16* __restrict__ wmod, const __nv_bfloat16* __restrict__ cvec, Scratch* __restrict__ gs,
                   const __nv_bfloat16* __restrict__ x, const __nv_bfloat16* __restrict__ wqkv,
                   const __nv_bfloat16* __restrict__ wo, const __nv_bfloat16* __restrict__ w1, const __nv_bfloat16* __restrict__ b1,
                   const __nv_bfloat16* __restrict__ w2, const __nv_bfloat16* __restrict__ b2,
                   __nv_bfloat16* __restrict__ out, const __grid_constant__ Maps maps) {
  extern __shared__ __align__(1024) uint8_t smem[];
  const uint32_t sb = smem_u32(smem);
  const uint32_t bars = sb + OFF_BAR;
  const int b = blockIdx.x, hf = b & 1;

  if (threadIdx.x >= 256) {
    asm volatile("setmaxnreg.dec.sync.aligned.u32 40;");
    const int warp = __shfl_sync(0xffffffffu, threadIdx.x >> 5, 0), lane = threadIdx.x & 31;
    const uint32_t epoch = ld_relaxed(&gs->epoch[b * FS]) + 1;
    uint32_t role = 64, old = 0;
    if (warp == 9 && lane == 0 && hf == 0) {
      uint32_t smid;
      asm volatile("mov.u32 %0, %%smid;" : "=r"(smid));
      const uint32_t t = smid >> 1;
      uint32_t gpc = t & 7, idx = t >> 3;
      if (t >= 32) { gpc = 1 + (t - 32) % 7; idx = 4 + (t - 32) / 7; }
      if (t >= 62) { gpc = 0; idx = t - 58; }
      if (t < 60 || (t >= 62 && t < 66)) {
        role = ((gpc + 7) & 7) * 8 + idx;
        old = atomicAdd(&gs->claim[role * FS], 1u);
      }
    }
    if (lane == 0) {
      if (warp == 8) {
        mbar_init(bars + 8 * B_GEMV, 1);
        fence_async_smem();
        if (b < 40) {
          mbar_expect(bars + 8 * B_GEMV, 40960);
          tma2d(sb + OFF_GEMV, &maps.wmod, 64 * (b >> 1), 320 * hf, bars + 8 * B_GEMV);
          tma2d(sb + OFF_GEMV + 20480, &maps.wmod, 64 * (b >> 1), 320 * hf + 160, bars + 8 * B_GEMV);
        }
        STAMP(37);
      }
      if (warp == 10) { mbar_init(bars + 8 * B_ROLE, 1); mbar_expect(bars + 8 * B_ROLE, 4); }
#pragma unroll 1
      for (int i = warp - 8; i < (int)B_LATE; i += 4) {
        if (i != B_GEMV) mbar_init(bars + 8 * i, (i == B_GEMVDONE || i == B_PEERRDY) ? 8 : 1);
        if (i >= B_H3) mbar_expect(bars + 8 * i, 14 * 128 * 16);
        if (i == B_GVP) mbar_expect(bars + 8 * i, 256);
      }
      asm volatile("fence.mbarrier_init.release.cluster;" ::: "memory");
      fence_async_smem();
    }
    __syncwarp();
    asm volatile("barrier.cluster.arrive.relaxed.aligned;" ::: "memory");
    asm volatile("bar.arrive 3, 384;" ::: "memory");
    asm volatile("barrier.cluster.wait.acquire.aligned;" ::: "memory");
    if (lane == 0) {
      if (warp == 9 && hf == 0) {
        if (role == 64 || old != epoch - 1) {
          if (role != 64) atomicSub(&gs->claim[role * FS], 1u);
#pragma unroll 1
          for (int n = 0; n < (1 << 16); n++) {
            role = n & 63;
            if (atomicAdd(&gs->claim[role * FS], 1u) == epoch - 1) break;
            atomicSub(&gs->claim[role * FS], 1u);
          }
        }
#pragma unroll
        for (int r = 0; r < 2; r++)
          asm volatile("st.async.shared::cluster.mbarrier::complete_tx::bytes.b32 [%0], %1, [%2];"
                       :: "r"(mapa(sb + OFF_ROLE, r)), "r"(role), "r"(mapa(bars + 8 * B_ROLE, r)) : "memory");
      } else {
        constexpr uint64_t M8 = (0xFFull << B_REMPTY) | (1ull << B_QKVDONE) | (1ull << B_KVSTG) | (1ull << B_OSTG) | (0xFull << B_OSTG1) |
                                (1ull << B_OPDONE) | (1ull << B_X1STG) | (1ull << B_MLP1DONE) |
                                (1ull << B_H3CONS) | (0xFull << B_PSTG) | (1ull << B_OUTSTG) | (1ull << B_W2D) | (1ull << B_GEMV2DONE);
        if (warp != 9) {
#pragma unroll 1
          for (int i = B_LATE + (warp == 8 ? 0 : warp - 9); i < (int)B_COUNT; i += 3) mbar_init(bars + 8 * i, (i >= B_OCONS || (i < 64 && ((M8 >> i) & 1))) ? 8 : 1);
          fence_async_smem();
        }
      }
    }
    __syncwarp();
    mbar_wait_cluster(bars + 8 * B_ROLE, 0);
    ROLE();
    if (lane == 0) {
      if (warp == 9) {
        STAMP(36);
#pragma unroll 1
        for (int j = 0; j < 10; j++) {
          if (j == 7) mbar_wait(bars + 8 * B_GEMVDONE, 0);
          mbar_expect(bars + 8 * (B_TILE + j), 16384);
          tma2d(sb + j * 16384, &maps.x, 64 * j, 128 * rb, bars + 8 * (B_TILE + j));
        }
        STAMP(33);
      } else {
#pragma unroll 1
        for (int j = 2 + (warp == 8 ? 0 : warp - 9); j < 16; j += 3)
          asm volatile("prefetch.tensormap [%0];" :: "l"(reinterpret_cast<const CUtensorMap*>(&maps) + j) : "memory");
      }
    }
    __syncwarp();
    asm volatile("bar.arrive 4, 384;" ::: "memory");
    asm volatile("bar.sync 5, 128;" ::: "memory");
    const uint32_t tag = epoch & 0xFFFFu;
    if ((warp & 1) == 0 && lane == 0) {
      const int cbig = 80 * g + 16 * hf, csm = 80 * g + 64 - 64 * hf;
      const bool two = ((g + 1) & 2) != 0;
#pragma unroll 1
      for (int s = (warp >> 1) & 1; s < 20; s += 2) {
        const int dep = nib(QD_LO, QD_HI, s);
        if (dep) wait_release(bars, dep - 1);
        else mbar_wait(bars + 8 * (B_TILE + BGATE), 0);
        const uint32_t dst = sb + unit_off(nib(QU_LO, QU_HI, s)), bar = bars + 8 * (B_RFULL + (s & 7));
        mbar_expect(bar, QKV_STAGE);
        if (two) tma4d(dst, &maps.wqkv64, cbig, 32 * s, 0, 0, bar);
        else tma3d(dst, &maps.wqkv128, cbig, 32 * s, 0, bar);
        tma3d(dst + 12288, &maps.wqkv32, csm, 32 * s, 0, bar);
        if (s == PFS) l2_prefetch(reinterpret_cast<const uint8_t*>(wqkv) + (size_t)(128 + 4 * b) * 3840, 4 * 3840);
        if (s == 9) {
#pragma unroll 1
          for (int r = 0; r < 5; r++) l2_prefetch(reinterpret_cast<const uint8_t*>(wmod) + (size_t)(5 * b + r) * 7680 + 2560, 5120);
        }
        if (s == 18) l2_prefetch(reinterpret_cast<const uint8_t*>(wo) + (size_t)b * 6400, 6400);
      }
    }
    __syncwarp();
    if (warp == 8) {
      if (lane == 0) {
        mbar_wait(bars + 8 * B_KVDONE, 0);
        l2_prefetch(reinterpret_cast<const uint8_t*>(w1) + (size_t)b * 17280, 17280);
        l2_prefetch(reinterpret_cast<const uint8_t*>(w2) + (size_t)b * 17280, 17280);
        mbar_wait(bars + 8 * B_OPDONE, 0);
        w1_stream(maps, sb, 0, p, hf, keep0, keep1, rb);
#pragma unroll 1
        for (int s = 0; s < 10; s++) {
          const int r = s & 3;
          const uint32_t dst = sb + (r == 0 ? OFF_W2B : r == 1 ? OFF_W2C : r == 2 ? OFF_W2A : OFF_W2D), bar = bars + 8 * (B_RFULL + (s & 7));
          if (s == 3) mbar_wait(bars + 8 * B_H3CONS, 0);
          else wait_release(bars, s >= 4 ? 36 + s : s == 0 ? 32 : s == 1 ? 34 : 37);
          const int ci = s >> 1, atom = ci == 0 ? 4 : ((p + ci) & 3);
          const int box = (s & 1) ? (1 - hf) : hf;
          mbar_expect(bar, W2_STAGE);
          tma2d(dst, &maps.w2, 320 * hf + 64 * atom, 448 * p + 224 * box, bar);
          STAMP(108 + s);
        }
      }
    } else if (warp == 9) {
      if (lane == 0) {
        mbar_wait(bars + 8 * B_QKVDONE, 0);
        if (rb > 0) {
#pragma unroll 1
          for (int h = 0; h < 4; h++) {
            const uint32_t bar = bars + 8 * (B_HALO + h);
            mbar_expect(bar, rb > 1 ? 2 * SLOT_BYTES : SLOT_BYTES);
            const uint32_t* f1 = &gs->kvflag[(cta - 8) * FS];
            const uint32_t* f2 = rb > 1 ? f1 - 8 * FS : f1;
            const uint32_t target = 4 * (epoch - 1) + h + 1;
            uint32_t v1, v2; int n = 0;
            do {
              v1 = ld_relaxed(f1); v2 = ld_relaxed(f2);
            } while (((int32_t)(v1 - target) < 0 || (int32_t)(v2 - target) < 0) && ++n < (1 << 16));
            asm volatile("fence.acquire.gpu;" ::: "memory");
            fence_async_global();
            bulk_load(sb + h * HEAD_BYTES + SLOT_BYTES, gs->kv + (size_t)((cta - 8) * 4 + h) * SLOT_BYTES, SLOT_BYTES, bar);
            if (rb > 1) bulk_load(sb + h * HEAD_BYTES, gs->kv + (size_t)((cta - 16) * 4 + h) * SLOT_BYTES, SLOT_BYTES, bar);
          }
        }
        mbar_wait(bars + 8 * B_KVDONE, 0);
        mbar_expect(bars + 8 * B_WO, 102400);
#pragma unroll 1
        for (int a = 0; a < 5; a++) {
          if (a == 3) mbar_wait(bars + 8 * B_GEMV2DONE, 0);
          tma4d(sb + OFF_WO + a * 20480, &maps.wo, 80 * g + 16 * a, 0, 0, 0, bars + 8 * B_WO);
        }
#pragma unroll 1
        for (int j = 0; j < 10; j++) {
          if (j == 0 || j == 5) {
            poll_ge(&gs->oflag[(rb * 2 + (j != 0)) * FS], 8 * epoch);
            fence_async_global();
            STAMP(56 + (j != 0) * 5);
          }
          if (j == 3) mbar_wait(bars + 8 * B_H2DONE, 0);
          if (j >= 6) mbar_wait(bars + 8 * (B_OCONS + j - 6), 0);
          mbar_expect(bars + 8 * (B_TILE + j), 16384);
          tma2d(sb + ((uint32_t)(OU >> (4 * j)) & 15u) * 16384, &maps.oLd, 64 * j, 128 * rb, bars + 8 * (B_TILE + j));
        }
        mbar_wait(bars + 8 * (B_OCONS + 4), 0);
        mbar_expect(bars + 8 * B_XOWN, 20480);
        tma2d(sb + OFF_OSTG, &maps.xOwn, 80 * g, 128 * rb, bars + 8 * B_XOWN);
        poll_ge(&gs->x1flag[rb * FS], 64 * epoch);
        STAMP(60);
        fence_async_global();
#pragma unroll 1
        for (int i = 0; i < 6; i++) {
          mbar_expect(bars + 8 * (B_TILE + i), 16384);
          tma2d(sb + i * 16384, &maps.x1Ld, 64 * x1_perm(i, keep0, keep1), 128 * rb, bars + 8 * (B_TILE + i));
        }
        mbar_wait(bars + 8 * B_H3CONS, 0);
        const int rh = rb * 2 + hf;
        poll_ge(&gs->p4flag[rh * FS], 4 * epoch);
        fence_async_global();
        mbar_expect(bars + 8 * (B_PIN + 3), 16384);
#pragma unroll 1
        for (int s = 0; s < 4; s++)
          bulk_load(sb + OFF_PIN4 + s * 4096, gs->part4 + (size_t)(rh * 4 + s) * 16384 + p * 4096, 4096, bars + 8 * (B_PIN + 3));
#pragma unroll 1
        for (int s = 0; s < 3; s++) {
          if (s == 1) mbar_wait(bars + 8 * B_W2D, 0);
          poll_ge(&gs->pflag[((rh * 4 + p) * 4 + s) * FS / 4], epoch);
          fence_async_global();
          mbar_expect(bars + 8 * (B_PIN + s), 16384);
          bulk_load(sb + OFF_PIN + s * 16384, gs->part + (size_t)((rh * 4 + p) * 3 + s) * 16384, 16384, bars + 8 * (B_PIN + s));
        }
      }
    } else if (warp == 10) {
      if (lane == 0) {
        mbar_wait(bars + 8 * B_KVSTG0, 0);
        STAMP(48);
        if (rb < 15) {
#pragma unroll 1
          for (int h = 0; h < 4; h++) {
            if (h == 1) mbar_wait(bars + 8 * B_KVSTG, 0);
            bulk_store(gs->kv + (size_t)(cta * 4 + h) * SLOT_BYTES, sb + h * HEAD_BYTES + 2 * SLOT_BYTES, SLOT_BYTES);
            bulk_commit();
            if (h == 0) STAMP(49);
            bulk_wait<0>();
            if (h == 0) STAMP(50);
            fence_rel(1);
            st_relaxed(&gs->kvflag[cta * FS], 4 * (epoch - 1) + h + 1);
            if (h == 0) STAMP(51);
          }
        }
        mbar_arrive(bars + 8 * B_KVDONE);
        STAMP(52);
#pragma unroll 1
        for (int sp = 0; sp < 2; sp++) {
          mbar_wait(bars + 8 * (B_OSTG + sp), 0);
          tma2d_store(&maps.oSt, 320 * sp + 40 * g, 128 * rb, sb + (sp ? OFF_OSTG1 : OFF_OSTG0));
          STAMP(53); bulk_commit(); bulk_wait<0>(); STAMP(54);
          fence_rel(2);
          red_add(&gs->oflag[(rb * 2 + sp) * FS], 1); STAMP(55);
        }
        mbar_wait(bars + 8 * B_X1STG, 0);
        w1_stream(maps, sb, 1, p, hf, keep0, keep1, rb);
        publish_partials(gs, sb, 0, rb * 2 + hf, p, epoch);
        mbar_wait(bars + 8 * B_OUTSTG, 0);
        tma2d_store(&maps.out, 320 * hf + 64 * p, 128 * rb, sb + 8 * 16384);
        bulk_commit(); bulk_wait<0>();
        st_relaxed(&gs->epoch[b * FS], epoch);
      }
    } else {
      if (b < 80) {
        if (lane == 0) {
          wait_release(bars, 7);
          wait_release(bars, 15);
          mbar_expect(bars + 8 * B_GEMV2, 40960);
#pragma unroll 1
          for (int j = 0; j < 4; j++) tma2d(sb + OFF_GEMV2 + j * 10240, &maps.wmod2, 1280 + 32 * b, 160 * j, bars + 8 * B_GEMV2);
        }
      }
      mbar_wait(bars + 8 * B_GEMV2DONE, 0);
      float c1 = 0.f, c2 = 0.f, c3 = 0.f, c4 = 0.f, c5 = 0.f;
#pragma unroll 1
      for (int i = lane; i < 160; i += 32) {
        uint4 va, vb; int n = 0;
        do {
          vb = ld_relaxed4(&gs->modw[1920 + 4 * i]);
          va = ld_relaxed4(&gs->modw[2560 + 4 * i]);
          if (++n > (1 << 16)) break;
        } while ((((va.x ^ tag) | (va.y ^ tag) | (va.z ^ tag) | (va.w ^ tag) | (vb.x ^ tag) | (vb.y ^ tag) | (vb.z ^ tag) | (vb.w ^ tag)) & 0xFFFFu) != 0);
        const uint32_t a01 = pack2(1.f + bhi(va.x), 1.f + bhi(va.y)), a23 = pack2(1.f + bhi(va.z), 1.f + bhi(va.w));
        const uint32_t addr = sb + OFF_AB + tab_off(4 * i);
        sts32(addr, a01); sts32(addr + 16, a23);
        sts32(addr + 8, (vb.x >> 16) | (vb.y & 0xFFFF0000u)); sts32(addr + 24, (vb.z >> 16) | (vb.w & 0xFFFF0000u));
        const float av[4] = {blo(a01), bhi(a01), blo(a23), bhi(a23)}, bv[4] = {bhi(vb.x), bhi(vb.y), bhi(vb.z), bhi(vb.w)};
#pragma unroll
        for (int e = 0; e < 4; e++) { c1 += av[e]; c2 = fmaf(av[e], av[e], c2); c3 = fmaf(av[e], bv[e], c3); c4 += bv[e]; c5 = fmaf(bv[e], bv[e], c5); }
      }
#pragma unroll
      for (int off = 1; off < 32; off <<= 1) {
        c1 += __shfl_xor_sync(0xffffffffu, c1, off); c2 += __shfl_xor_sync(0xffffffffu, c2, off); c3 += __shfl_xor_sync(0xffffffffu, c3, off);
        c4 += __shfl_xor_sync(0xffffffffu, c4, off); c5 += __shfl_xor_sync(0xffffffffu, c5, off);
      }
      if (lane == 0) STAMP(123);
      if (lane == 0) { stsf(sb + OFF_CC, c1); stsf(sb + OFF_CC + 4, c2); stsf(sb + OFF_CC + 8, c3); stsf(sb + OFF_CC + 12, c4); stsf(sb + OFF_CC + 16, c5); }
      if (lane < 20) {
        const uint4 v = poll_tag4(&gs->modw[1280 + 80 * g + 4 * lane], tag);
        stsf(sb + OFF_GA + lane * 16, bhi(v.x)); stsf(sb + OFF_GA + lane * 16 + 4, bhi(v.y));
        stsf(sb + OFF_GA + lane * 16 + 8, bhi(v.z)); stsf(sb + OFF_GA + lane * 16 + 12, bhi(v.w));
      }
      __syncwarp();
#pragma unroll 1
      for (int ks = 0; ks < 5; ks++) {
        const uint4 t = lds128(sb + OFF_AB + (5 * g + ks) * 64 + (lane & 3) * 16);
        const int n = lane >> 2;
        uint32_t o[2];
#pragma unroll
        for (int u = 0; u < 2; u++) {
          const uint32_t aw = u ? t.y : t.x, bw = u ? t.w : t.z;
          const float m0 = blo(aw) * ((n & 4) ? blo(bw) : blo(aw)), m1 = bhi(aw) * ((n & 4) ? bhi(bw) : bhi(aw));
          const uint32_t hi = pack2(m0, m1);
          o[u] = n == 0 ? 0x3F803F80u : n == 1 ? aw : n >= 6 ? 0u : (n & 1) ? pack2(m0 - blo(hi), m1 - bhi(hi)) : hi;
        }
        asm volatile("st.shared.v2.b32 [%0], {%1,%2};" :: "r"(sb + OFF_LIN + ks * 256 + lane * 8), "r"(o[0]), "r"(o[1]) : "memory");
      }
#pragma unroll 1
      for (int i = lane; i < 112; i += 32) {
        const int n = 2 * i;
        const int f = hf == 0 ? 448 * p + n : (n < 192 ? 448 * p + 256 + n : 448 * p + 32 + n);
        sts32(sb + OFF_B1 + i * 4, f < FF ? *reinterpret_cast<const uint32_t*>(b1 + f) : 0u);
      }
      __syncwarp();
      if (lane == 0) mbar_arrive(bars + 8 * B_TAB2);
      if (lane == 0) STAMP(120);
      const int col = 320 * hf + (lane < 16 ? 64 * p + 4 * lane : 256 + 4 * (lane - 16));
      const uint4 vg = poll_tag4(&gs->modw[3200 + col], tag);
      const uint2 vb2 = *reinterpret_cast<const uint2*>(b2 + col);
      mbar_wait(bars + 8 * B_MLP1DONE, 0);
      const uint32_t fa = sb + OFF_FIN + lane * 16;
      sts128(fa, vg.x & 0xFFFF0000u, vg.y & 0xFFFF0000u, vg.z & 0xFFFF0000u, vg.w & 0xFFFF0000u);
      sts128(fa + 512, vb2.x << 16, vb2.x & 0xFFFF0000u, vb2.y << 16, vb2.y & 0xFFFF0000u);
      __syncwarp();
      if (lane == 0) { mbar_arrive(bars + 8 * B_FIN); publish_partials(gs, sb, 1, rb * 2 + hf, p, epoch); }
    }
  } else {
    asm volatile("setmaxnreg.inc.sync.aligned.u32 232;");
    RowC rc;
    {
      IDS();
      const uint32_t cw = __ldg(reinterpret_cast<const uint32_t*>(cvec) + tid), cw2 = __ldg(reinterpret_cast<const uint32_t*>(cvec) + 256 + (tid & 63));
      const uint32_t epoch0 = ld_relaxed(&gs->epoch[b * FS]);
      asm volatile("barrier.cluster.arrive.relaxed.aligned;" ::: "memory");
      const uint32_t tag = (epoch0 + 1) & 0xFFFFu;
      if (tid == 0) sts32(sb + OFF_ROLE + 4, tag);
      {
        const uint32_t sa = sb + OFF_SC + (tid >> 3) * 32 + (tid & 3) * 8 + ((tid >> 2) & 1) * 4;
        sts32(sa, pack2(silu_f(blo(cw)), silu_f(bhi(cw))));
        if (tid < 64) sts32(sa + 1024, pack2(silu_f(blo(cw2)), silu_f(bhi(cw2))));
      }
      asm volatile("bar.sync 3, 384;" ::: "memory");
      uint32_t gdep = 0;
      if (b < 40) {
        float d0[4] = {0.f, 0.f, 0.f, 0.f}, d1[4] = {0.f, 0.f, 0.f, 0.f};
        mbar_wait(bars + 8 * B_GEMV, 0);
        if (tid == 0) STAMP(42);
        const uint32_t wa = sb + OFF_GEMV + lane * 128 + ((warp ^ (lane & 7)) << 4);
#pragma unroll
        for (int i = 0; i < 10; i++) {
          uint32_t w4v[4];
          ldsm4t(w4v, wa + i * 4096);
          const float2 s0 = ldsf2(sb + OFF_SC + hf * 640 + i * 64 + q * 8), s1 = ldsf2(sb + OFF_SC + hf * 640 + i * 64 + 32 + q * 8);
          const uint32_t a0[4] = {__float_as_uint(s0.x), 0u, __float_as_uint(s0.y), 0u}, a1[4] = {__float_as_uint(s1.x), 0u, __float_as_uint(s1.y), 0u};
          mma16(d0, a0, w4v[0], w4v[1]);
          mma16(d1, a1, w4v[2], w4v[3]);
        }
        const float v0 = d0[0] + d1[0], v1 = d0[1] + d1[1];
        gdep = __float_as_uint(v0);
        asm volatile("barrier.cluster.wait.acquire.aligned;" ::: "memory");
        if (hf) {
          if (lane < 4)
            asm volatile("st.async.shared::cluster.mbarrier::complete_tx::bytes.v2.f32 [%0], {%1,%2}, [%3];"
                         :: "r"(mapa(sb + OFF_GVP + warp * 32 + q * 8, 0)), "f"(v0), "f"(v1), "r"(mapa(bars + 8 * B_GVP, 0)) : "memory");
        } else {
          mbar_wait_cluster(bars + 8 * B_GVP, 0);
          const float2 pv = ldsf2(sb + OFF_GVP + warp * 32 + q * 8);
          const uint32_t w = pack2(v0 + pv.x, v1 + pv.y);
          if (lane < 4)
            asm volatile("st.relaxed.gpu.global.v2.u32 [%0], {%1,%2};" :: "l"(&gs->modw[32 * b + 8 * warp + 2 * q]), "r"((w << 16) | tag), "r"((w & 0xFFFF0000u) | tag) : "memory");
        }
        if (tid == 0) STAMP(40);
      } else {
        asm volatile("barrier.cluster.wait.acquire.aligned;" ::: "memory");
      }
      if (lane == 0) mbar_arrive(dep_on(bars + 8 * B_GEMVDONE, gdep));
      uint4 mv0 = make_uint4(0, 0, 0, 0), mv1 = mv0;
      {
        const uint32_t arow = sb + (uint32_t)(16 * warp + (lane & 15)) * 128u;
        const uint32_t c0 = ((lane >> 4) ^ (lane & 7)) << 4;
        float cs[2][4], g0[2][4], g1[2][4];
#pragma unroll
        for (int i = 0; i < 2; i++)
#pragma unroll
          for (int e = 0; e < 4; e++) { cs[i][e] = 0.f; g0[i][e] = 0.f; g1[i][e] = 0.f; }
#pragma unroll 1
        for (int j = 0; j < 10; j += 2) {
          mbar_wait(bars + 8 * (B_TILE + j), 0);
          mbar_wait(bars + 8 * (B_TILE + j + 1), 0);
          if (tid == 0 && (j == 0 || j == 8)) STAMP(34 + (j != 0) * 7);
          uint32_t a[8][4];
#pragma unroll
          for (int ks = 0; ks < 8; ks++) ldsm4(a[ks], arow + (j + (ks >> 2)) * 16384 + (c0 ^ (32 * (ks & 3))));
          if (j == 6) { mv0 = ld_relaxed4(&gs->modw[4 * tid]); mv1 = ld_relaxed4(&gs->modw[4 * (256 + (tid & 63))]); }
#pragma unroll
          for (int ks = 0; ks < 8; ks++) {
            mma16(cs[ks & 1], a[ks], 0x3F803F80u, 0x3F803F80u);
            mma16(g0[ks & 1], a[ks], a[ks][0], a[ks][2]);
            mma16(g1[ks & 1], a[ks], a[ks][1], a[ks][3]);
          }
        }
        const int src = (lane & ~3) | (gq >> 1);
        const float sq0 = __shfl_sync(0xffffffffu, (gq & 1) ? g0[0][1] + g0[1][1] : g0[0][0] + g0[1][0], src);
        const float sq1 = __shfl_sync(0xffffffffu, (gq & 1) ? g1[0][3] + g1[1][3] : g1[0][2] + g1[1][2], src);
        const float mu0 = (cs[0][0] + cs[1][0]) * (1.f / DM), mu1 = (cs[0][2] + cs[1][2]) * (1.f / DM);
        const float r0 = rsqrtf(fmaxf(sq0 * (1.f / DM) - mu0 * mu0, 0.f) + 1e-5f), r1 = rsqrtf(fmaxf(sq1 * (1.f / DM) - mu1 * mu1, 0.f) + 1e-5f);
        rc.P0 = dup2(r0); rc.Q0 = dup2(-mu0 * r0); rc.P1 = dup2(r1); rc.Q1 = dup2(-mu1 * r1);
        rc.R0 = rc.R1 = rc.T0 = rc.T1 = 0u;
      }
    if (stamp) STAMP(0 + wg);
#pragma unroll 1
    for (int i = tid; i < 320; i += 256) {
      uint4 v = i < 256 ? mv0 : mv1;
      if ((((v.x ^ tag) | (v.y ^ tag) | (v.z ^ tag) | (v.w ^ tag)) & 0xFFFFu) != 0) v = poll_tag4(&gs->modw[4 * i], tag);
      const bool isa = i >= 160;
      const float one = isa ? 1.f : 0.f;
      const uint32_t addr = sb + OFF_AB + tab_off(4 * (isa ? i - 160 : i)) + (isa ? 0 : 8);
      sts32(addr, pack2(one + bhi(v.x), one + bhi(v.y)));
      sts32(addr + 16, pack2(one + bhi(v.z), one + bhi(v.w)));
    }
    asm volatile("bar.sync 4, 384;" ::: "memory");
    if (stamp) STAMP(2 + wg);
    }

    uint32_t qo[24];
    {
      IDS();
      mbar_wait_cluster(bars + 8 * B_ROLE, 0);
      ROLE();
      float acc1[96], acc2[24];
      gemm_norm<48, false>(acc1, acc2, sb, warp, lane, rc, 0, 0, ((g + 1) & 2) != 0);
      if (stamp) STAMP(4 + wg);
      cons_sync();
      if (lane == 0) mbar_arrive(bars + 8 * B_QKVDONE);
      const uint32_t rbase = sb + 2 * SLOT_BYTES + row0 * 80 + 4 * q;
      const uint32_t strk = q < 2 ? 32u : HEAD_BYTES + 40u - 8u, strv = q < 2 ? 72u : HEAD_BYTES - 8u;
      uint32_t qf[20];
#pragma unroll
      for (int pass = 0; pass < 3; pass++) {
#pragma unroll
        for (int part = (pass == 2 ? 0 : 1); part < (pass == 2 ? 1 : 3); part++)
#pragma unroll
          for (int blk = (pass == 1 ? 3 : 0); blk < (pass == 0 ? 3 : 10); blk++) {
            const int ie = 2 * blk, io = (2 * blk + 16) % 20;
            const float* ae = ie < 16 ? &acc1[32 * part + 2 * ie] : &acc2[8 * part + 2 * (ie - 16)];
            const float* ao = io < 16 ? &acc1[32 * part + 2 * io] : &acc2[8 * part + 2 * (io - 16)];
            const uint32_t e0 = pack2(ae[0], ae[1]), e1 = pack2(ae[2], ae[3]), o0 = pack2(ao[0], ao[1]), o1 = pack2(ao[2], ao[3]);
            const uint32_t v0 = hf ? o0 : e0, v1 = hf ? o1 : e1;
            if (part == 0) { qf[2 * blk] = v0; qf[2 * blk + 1] = v1; }
            else {
              const int hd = (8 * blk) / 20, d = 8 * blk - 20 * hd;
              const uint32_t ad = rbase + hd * HEAD_BYTES + ((blk == 2 || blk == 7) ? (part == 1 ? strk : strv) : (uint32_t)((((hd & 1) ^ (part == 2)) ? 40 : 0) + 2 * d));
              sts32(ad, v0); sts32(ad + 640, v1);
            }
          }
        if (pass < 2) {
          fence_async_smem();
          __syncwarp();
          if (lane == 0) mbar_arrive(bars + 8 * (pass == 0 ? B_KVSTG0 : B_KVSTG));
        }
      }
#pragma unroll
      for (int hp = 0; hp < 2; hp++) {
        const int o10 = 10 * hp;
        qo[12 * hp + 0] = qf[o10 + 0]; qo[12 * hp + 1] = qf[o10 + 1]; qo[12 * hp + 2] = qf[o10 + 2]; qo[12 * hp + 3] = qf[o10 + 3];
        qo[12 * hp + 4] = q < 2 ? qf[o10 + 4] : 0u; qo[12 * hp + 5] = q < 2 ? qf[o10 + 5] : 0u;
        qo[12 * hp + 6] = qf[o10 + 6]; qo[12 * hp + 7] = qf[o10 + 7]; qo[12 * hp + 8] = qf[o10 + 8]; qo[12 * hp + 9] = qf[o10 + 9];
        qo[12 * hp + 10] = q < 2 ? 0u : qf[o10 + 4]; qo[12 * hp + 11] = q < 2 ? 0u : qf[o10 + 5];
      }
      if (rb < 2) {
        const int n16 = (rb == 0 ? 2 * SLOT_BYTES : SLOT_BYTES) / 16;
#pragma unroll 1
        for (int h = 0; h < 4; h++)
#pragma unroll 1
          for (int i = tid; i < n16; i += 256) sts128(sb + h * HEAD_BYTES + i * 16, 0u, 0u, 0u, 0u);
      }
      float gv0 = 0.f, gv1 = 0.f;
      if (b < 80) {
        float d0[4] = {0.f, 0.f, 0.f, 0.f}, d1[4] = {0.f, 0.f, 0.f, 0.f};
        const uint32_t wa = sb + OFF_GEMV2 + wg * 20480 + lane * 64 + ((w4 ^ ((lane >> 1) & 3)) << 4);
        mbar_wait(bars + 8 * B_GEMV2, 0);
        if (tid == 0) STAMP(118);
#pragma unroll
        for (int i = 0; i < 10; i++) {
          uint32_t w4v[4];
          ldsm4t(w4v, wa + i * 2048);
          const float2 s0 = ldsf2(sb + OFF_SC + wg * 640 + i * 64 + q * 8), s1 = ldsf2(sb + OFF_SC + wg * 640 + i * 64 + 32 + q * 8);
          const uint32_t a0[4] = {__float_as_uint(s0.x), 0u, __float_as_uint(s0.y), 0u}, a1[4] = {__float_as_uint(s1.x), 0u, __float_as_uint(s1.y), 0u};
          mma16(d0, a0, w4v[0], w4v[1]);
          mma16(d1, a1, w4v[2], w4v[3]);
        }
        gv0 = d0[0] + d1[0]; gv1 = d0[1] + d1[1];
        if (wg == 1 && lane < 4) { stsf(sb + OFF_GVP + w4 * 32 + q * 8, gv0); stsf(sb + OFF_GVP + w4 * 32 + q * 8 + 4, gv1); }
      }
      cons_sync();
      if (b < 80 && wg == 0 && lane < 4) {
        const float2 pv = ldsf2(sb + OFF_GVP + w4 * 32 + q * 8);
        const uint32_t w = pack2(gv0 + pv.x, gv1 + pv.y);
        const uint32_t tag = lds32(sb + OFF_ROLE + 4);
        asm volatile("st.relaxed.gpu.global.v2.u32 [%0], {%1,%2};" :: "l"(&gs->modw[1280 + 32 * b + 8 * w4 + 2 * q]), "r"((w << 16) | tag), "r"((w & 0xFFFF0000u) | tag) : "memory");
        gv0 = pv.x;
      }
      __syncwarp();
      if (lane == 0) mbar_arrive(dep_on(bars + 8 * B_GEMV2DONE, __float_as_uint(gv0)));
      if (tid == 0) STAMP(119);
      if (stamp) STAMP(6 + wg);
    }
    {
      IDS();
      ROLE();
      uint32_t msk[4];
#pragma unroll
      for (int i = 0; i < 4; i++) {
        const int r = gq + 8 * (i & 1), c = 8 * (i >> 1) + 2 * q;
        msk[i] = (c > r ? 0xFFFFu : 0u) | (c + 1 > r ? 0xFFFF0000u : 0u);
      }
      const int jmin = 16 - (8 * rb + warp);
      const uint32_t wb = sb + warp * 1280;
#pragma unroll 1
      for (int h = 0; h < 4; h++) {
        if (rb > 0) mbar_wait(bars + 8 * (B_HALO + h), 0);
        if (h == 0 && stamp) STAMP(8 + wg);
        if (h == 0 && wg == 1) asm volatile("bar.sync 2, 256;" ::: "memory");
        attn_head(qo, wb + h * HEAD_BYTES, h & 1, lane, jmin, msk, h == 0 && wg == 0);
        if (tid == 0) STAMP(44 + h);
        if (h & 1) {
          mbar_wait(bars + 8 * (h == 1 ? B_H0DONE : B_H2DONE), 0);
          mbar_wait(bars + 8 * B_KVDONE, 0);
          const uint32_t base = sb + (h == 1 ? OFF_OSTG0 : OFF_OSTG1) + row0 * 80 + 4 * q;
          if (q >= 2) { sts32(base - 8, qo[12]); sts32(base + 632, qo[13]); }
          sts32(base + 8, qo[14]); sts32(base + 648, qo[15]); sts32(base + 24, qo[16]); sts32(base + 664, qo[17]);
          sts32(base + 40, qo[18]); sts32(base + 680, qo[19]); sts32(base + 56, qo[20]); sts32(base + 696, qo[21]);
          if (q < 2) { sts32(base + 72, qo[22]); sts32(base + 712, qo[23]); }
          fence_async_smem();
        }
        __syncwarp();
        if (lane == 0) mbar_arrive(dep_on(bars + 8 * (h == 0 ? B_H0DONE : h == 1 ? B_OSTG : h == 2 ? B_H2DONE : B_OSTG1), qo[23]));
      }
      if (stamp) STAMP(10 + wg);
    }
    {
    IDS();
    ROLE();
    {
      float acc[40];
      mbar_wait(bars + 8 * B_WO, 0);
#pragma unroll 1
      for (int j = 0; j < 10; j++) {
        if (j == 5) { wg_wait<0>(); if (lane == 0) mbar_arrive(bars + 8 * (B_OCONS + 4)); if (stamp) STAMP(106 + wg); }
        mbar_wait(bars + 8 * (B_TILE + j), 1);
        if (j == 5 && stamp) STAMP(12 + wg);
        const uint32_t at = sb + ((uint32_t)(OU >> (4 * j)) & 15u) * 16384 + wg * 8192;
        wg_fence();
#pragma unroll
        for (int ks = 0; ks < 4; ks++)
          wgmma_ss_n80(acc, mkdesc(at + ks * 32, 16, 1024, 1), mkdesc(sb + OFF_WO + (64 * j + 16 * ks) * 32, 20480, 256, 3), (j | ks) != 0);
        wg_commit();
        wg_wait<1>();
        if (j >= 1 && j <= 4 && lane == 0) mbar_arrive(bars + 8 * (B_OCONS + j - 1));
      }
      mbar_wait(bars + 8 * B_TAB2, 0);
      mbar_wait(bars + 8 * B_XOWN, 0);
      uint32_t xw[20];
      float2 gav[10], lbv[5], avv[5];
#pragma unroll
      for (int nb = 0; nb < 10; nb++) {
        gav[nb] = ldsf2(sb + OFF_GA + (8 * nb + 2 * q) * 4);
        xw[2 * nb] = lds32(sb + OFF_OSTG + row0 * 160 + (8 * nb + 2 * q) * 2); xw[2 * nb + 1] = lds32(sb + OFF_OSTG + row0 * 160 + (8 * nb + 2 * q) * 2 + 1280);
      }
#pragma unroll
      for (int ks = 0; ks < 5; ks++) { lbv[ks] = ldsf2(sb + OFF_LIN + ks * 256 + lane * 8); avv[ks] = ldsf2(sb + OFF_AB + (5 * g + ks) * 64 + q * 16); }
      __syncwarp();
      wg_wait<0>();
      fence_regs(acc);
      if (lane == 0) mbar_arrive(bars + 8 * B_OPDONE);
      if (stamp) STAMP(14 + wg);
#pragma unroll
      for (int nb = 0; nb < 10; nb++) {
        const float2 ga = gav[nb];
        const uint32_t sa = sb + OFF_OSTG + row0 * 160 + (8 * nb + 2 * q) * 2;
        const uint32_t x0 = xw[2 * nb], x1v = xw[2 * nb + 1];
        xw[2 * nb] = pack2(fmaf(ga.x, acc[4 * nb], blo(x0)), fmaf(ga.y, acc[4 * nb + 1], bhi(x0)));
        xw[2 * nb + 1] = pack2(fmaf(ga.x, acc[4 * nb + 2], blo(x1v)), fmaf(ga.y, acc[4 * nb + 3], bhi(x1v)));
        sts32(sa, xw[2 * nb]); sts32(sa + 1280, xw[2 * nb + 1]);
      }
      fence_async_smem();
      __syncwarp();
      if (lane == 0) { tma2d_store(&maps.x1St, 80 * g, 128 * rb + 16 * warp, sb + OFF_OSTG + warp * 2560); bulk_commit(); }
      float lin[4] = {0.f, 0.f, 0.f, 0.f}, g0[4] = {0.f, 0.f, 0.f, 0.f}, g1[4] = {0.f, 0.f, 0.f, 0.f}, h0[4] = {0.f, 0.f, 0.f, 0.f}, h1[4] = {0.f, 0.f, 0.f, 0.f};
#pragma unroll
      for (int ks = 0; ks < 5; ks++) {
        const uint32_t a[4] = {xw[4 * ks], xw[4 * ks + 1], xw[4 * ks + 2], xw[4 * ks + 3]};
        const float2 lb = lbv[ks], av = avv[ks];
        const uint32_t xa[4] = {hmul2(a[0], __float_as_uint(av.x)), hmul2(a[1], __float_as_uint(av.x)), hmul2(a[2], __float_as_uint(av.y)), hmul2(a[3], __float_as_uint(av.y))};
        mma16(lin, a, __float_as_uint(lb.x), __float_as_uint(lb.y));
        mma16(g0, a, a[0], a[2]); mma16(g1, a, a[1], a[3]);
        mma16(h0, xa, xa[0], xa[2]); mma16(h1, xa, xa[1], xa[3]);
      }
      {
        const int src = (lane & ~3) | (gq >> 1);
        const float xx0 = __shfl_sync(0xffffffffu, (gq & 1) ? g0[1] : g0[0], src), xx1 = __shfl_sync(0xffffffffu, (gq & 1) ? g1[3] : g1[2], src);
        const float aa0 = __shfl_sync(0xffffffffu, (gq & 1) ? h0[1] : h0[0], src), aa1 = __shfl_sync(0xffffffffu, (gq & 1) ? h1[3] : h1[2], src);
        const float p0 = lin[0] + lin[1], p1 = lin[2] + lin[3];
        const float n0 = __shfl_down_sync(0xffffffffu, p0, 1), n1 = __shfl_down_sync(0xffffffffu, p1, 1);
        if ((q & 1) == 0) {
          const uint32_t ep = lds32(sb + OFF_ROLE + 4);
          uint32_t* dst = reinterpret_cast<uint32_t*>(gs->stats) + ((size_t)cta * 128 + row0) * 8 + 2 * q;
          stat_put(dst, q ? p0 : lin[0], q ? xx0 : lin[1], q ? aa0 : n0, ep);
          stat_put(dst + 64, q ? p1 : lin[2], q ? xx1 : lin[3], q ? aa1 : n1, ep);
        }
      }
      if (stamp) STAMP(16 + wg);
      if (lane == 0) {
        bulk_wait<0>();
        fence_rel(2);
        red_add(&gs->x1flag[rb * FS], 1);
        mbar_arrive(bars + 8 * B_X1STG);
      }
      __syncwarp();
      cons_sync();
      if (tid == 0) STAMP(59);
    }
    }
    uint32_t hA[56];
    {
      IDS();
      ROLE();
      float acc1[96], acc2[16];
#pragma unroll
      for (int nb = 0; nb < 28; nb++) {
        const uint32_t bw = lds32(sb + OFF_B1 + (4 * nb + q) * 4);
        float* a = nb < 24 ? &acc1[4 * nb] : &acc2[4 * (nb - 24)];
        a[0] = blo(bw); a[1] = bhi(bw); a[2] = blo(bw); a[3] = bhi(bw);
      }
      {
        float u0, u1, u2;
        {
          const uint32_t ep = lds32(sb + OFF_ROLE + 4);
          const uint32_t* sp = reinterpret_cast<const uint32_t*>(gs->stats) + ((size_t)rb * 1024 + 16 * warp) * 8 + lane * 4;
          uint32_t miss; int n = 0;
          do {
            uint4 v[8];
#pragma unroll
            for (int u = 0; u < 8; u++)
              asm volatile("{ .reg .b64 lo, hi; ld.relaxed.gpu.global.v2.b64 {lo, hi}, [%4]; mov.b64 {%0,%1}, lo; mov.b64 {%2,%3}, hi; }"
                           : "=r"(v[u].x), "=r"(v[u].y), "=r"(v[u].z), "=r"(v[u].w) : "l"(sp + u * 1024) : "memory");
            miss = 0; u0 = 0.f; u1 = 0.f; u2 = 0.f;
#pragma unroll
            for (int u = 0; u < 8; u++) {
              miss |= (v[u].w ^ ep) | ((v[u].x ^ ep) & 7u) | ((v[u].y ^ (ep >> 3)) & 7u);
              u0 += __uint_as_float(v[u].x); u1 += __uint_as_float(v[u].y); u2 += __uint_as_float(v[u].z);
            }
          } while (miss != 0 && ++n < (1 << 16));
          __syncwarp();
        }
        const float w0 = __shfl_xor_sync(0xffffffffu, u0, 1), w1 = __shfl_xor_sync(0xffffffffu, u1, 1), w2 = __shfl_xor_sync(0xffffffffu, u2, 1);
        const bool od = lane & 1;
        const float sx = od ? w0 : u0, sxa = od ? w1 : u1, sxa2 = od ? w2 : u2, sxab = od ? u0 : w0, sxx = od ? u1 : w1, saa = od ? u2 : w2;
        const float4 cc = ldsf4(sb + OFF_CC);
        const float c5 = ldsf(sb + OFF_CC + 16);
        constexpr float ID = 1.f / DM;
        const float mu = sx * ID, r = rsqrtf(fmaxf(sxx * ID - mu * mu, 0.f) + 1e-5f);
        const float m2 = (r * (sxa - mu * cc.x) + cc.w) * ID;
        const float e2 = (r * r * (saa - 2.f * mu * sxa2 + mu * mu * cc.y) + 2.f * r * (sxab - mu * cc.z) + c5) * ID;
        const float r2 = rsqrtf(fmaxf(e2 - m2 * m2, 0.f) + 1e-5f);
        const uint32_t pq = pack2(r * r2, -mu * r * r2), rt = pack2(r2, -m2 * r2);
        const uint32_t pq0 = __shfl_sync(0xffffffffu, pq, 2 * gq), rt0 = __shfl_sync(0xffffffffu, rt, 2 * gq);
        const uint32_t pq1 = __shfl_sync(0xffffffffu, pq, 2 * gq + 16), rt1 = __shfl_sync(0xffffffffu, rt, 2 * gq + 16);
        rc.P0 = __byte_perm(pq0, 0, 0x1010); rc.Q0 = __byte_perm(pq0, 0, 0x3232); rc.R0 = __byte_perm(rt0, 0, 0x1010); rc.T0 = __byte_perm(rt0, 0, 0x3232);
        rc.P1 = __byte_perm(pq1, 0, 0x1010); rc.Q1 = __byte_perm(pq1, 0, 0x3232); rc.R1 = __byte_perm(rt1, 0, 0x1010); rc.T1 = __byte_perm(rt1, 0, 0x3232);
      }
      if (stamp) STAMP(18 + wg);
      gemm_norm<32, true>(acc1, acc2, sb, warp, lane, rc, keep0, keep1, false);
      if (stamp) STAMP(20 + wg);
      if (lane == 0) { mbar_arrive(bars + 8 * B_MLP1DONE); mbar_arrive_cluster(mapa(bars + 8 * B_PEERRDY, hf ^ 1)); }
      const uint32_t rdst = mapa(sb + OFF_PIN + tid * 16, hf ^ 1), rbar = mapa(bars + 8 * (B_H3 + wg), hf ^ 1);
#pragma unroll
      for (int s = 0; s < 14; s++) {
        const float* a = s < 12 ? &acc1[8 * s] : &acc2[8 * (s - 12)];
#pragma unroll
        for (int e = 0; e < 4; e++) hA[4 * s + e] = pack2(gelu_tanh(a[2 * e]), gelu_tanh(a[2 * e + 1]));
        if (s == 3) mbar_wait_cluster(bars + 8 * B_PEERRDY, 0);
        if (s >= 3 && (s & 1) && (s - 3) / 2 < NSEND)
          st_async4(rdst + (s - 3) / 2 * 4096, &hA[4 * ((s - 3) / 2)], rbar);
      }
      fence_regs(hA);
      if (stamp) STAMP(22 + wg);
    }
    {
      IDS();
      uint32_t hB[56];
      float accA[32], accB[32];
      const uint32_t rdst = mapa(sb + OFF_PIN + tid * 16, hf ^ 1), rbar = mapa(bars + 8 * (B_H3 + wg), hf ^ 1);
      const uint32_t roff_own = hf * 256, roff_peer = (hf ^ 1) * 256;
      const uint32_t rowaddr = (uint32_t)(16 * warp + (lane & 15)) * 128u, c0 = ((lane >> 4) ^ (lane & 7)) << 4;
#pragma unroll
      for (int ci = 0; ci < 5; ci++) {
        float (&cur)[32] = (ci & 1) ? accB : accA;
        float (&prv)[32] = (ci & 1) ? accA : accB;
        constexpr uint32_t SLOT[4] = {OFF_W2B, OFF_W2C, OFF_W2A, OFF_W2D};
        if (ci == 4) {
          mbar_wait(bars + 8 * B_FIN, 0);
#pragma unroll
          for (int nb = 0; nb < 8; nb++) {
            const float2 t = ldsf2(sb + OFF_FIN + 512 + (8 * nb + 2 * q) * 4);
            cur[4 * nb] = t.x; cur[4 * nb + 1] = t.y; cur[4 * nb + 2] = t.x; cur[4 * nb + 3] = t.y;
          }
          fence_regs(cur);
        }
        {
          const int s = 2 * ci;
          const uint64_t d0 = mkdesc(sb + SLOT[s & 3], 16, 1024, 1);
          const uint64_t dlo = d0 + roff_own, dhi = d0 - 6 * roff_own;
          mbar_wait(bars + 8 * (B_RFULL + (s & 7)), ((40 + s) >> 3) & 1);
          wg_fence();
#pragma unroll
          for (int ks = 0; ks < 14; ks++) {
            wgmma_rs_n64(cur, &hA[4 * ks], (ks < 12 ? dlo : dhi) + ks * 128, ci == 4 || ks != 0);
            if (ci == 0 && ks + NSEND < 14) st_async4(rdst + (ks + NSEND) * 4096, &hA[4 * (ks + NSEND)], rbar);
          }
          wg_commit();
        }
        if (ci == 0) {
          mbar_wait_cluster(bars + 8 * (B_H3 + wg), 0);
#pragma unroll
          for (int s = 0; s < 14; s++) {
            const uint4 v = lds128(sb + OFF_PIN + s * 4096 + tid * 16);
            hB[4 * s] = v.x; hB[4 * s + 1] = v.y; hB[4 * s + 2] = v.z; hB[4 * s + 3] = v.w;
          }
          fence_regs(hB);
          uint32_t hx = 0;
#pragma unroll
          for (int s = 0; s < 14; s++) hx ^= hB[4 * s];
          hx = __shfl_xor_sync(0xffffffffu, hx, 16);
          if (lane == 0) mbar_arrive(dep_on(bars + 8 * B_H3CONS, hx));
        } else {
          wg_wait<1>();
          fence_regs(prv);
          if (lane == 0) mbar_arrive(bars + 8 * (ci == 4 ? B_W2D : B_REMPTY + ((2 * ci - 1) & 7)));
          if (ci >= 3) mbar_wait(bars + 8 * (B_PFREE + ci - 3), 0);
          const uint32_t sa = sb + OFF_PSTG + ((ci - 1) & 1) * 16384 + rowaddr;
#pragma unroll
          for (int j = 0; j < 4; j++)
            stsm4(sa + (c0 ^ (32 * j)), pack2(prv[8 * j], prv[8 * j + 1]), pack2(prv[8 * j + 2], prv[8 * j + 3]),
                  pack2(prv[8 * j + 4], prv[8 * j + 5]), pack2(prv[8 * j + 6], prv[8 * j + 7]));
          fence_async_smem();
          __syncwarp();
          if (lane == 0) mbar_arrive(bars + 8 * (B_PSTG + ci - 1));
        }
        {
          const int s = 2 * ci + 1;
          const uint64_t d0 = mkdesc(sb + SLOT[s & 3], 16, 1024, 1);
          const uint64_t dlo = d0 + roff_peer, dhi = d0 - 6 * roff_peer;
          mbar_wait(bars + 8 * (B_RFULL + (s & 7)), ((40 + s) >> 3) & 1);
          wg_fence();
#pragma unroll
          for (int ks = 0; ks < 14; ks++) wgmma_rs_n64(cur, &hB[4 * ks], (ks < 12 ? dlo : dhi) + ks * 128, 1);
          wg_commit();
          if (ci < 4) {
            wg_wait<1>();
            if (lane == 0) mbar_arrive(bars + 8 * (B_REMPTY + ((2 * ci) & 7)));
          }
        }
      }
      if (stamp) STAMP(24 + wg);
      ROLE();
      mbar_wait(bars + 8 * (B_PIN + 3), 0);
      {
        const int r = tid >> 3, ch = tid & 7;
        const uint32_t off = r * 128 + ((ch ^ (r & 7)) << 4);
        const float4 gb0 = ldsf4(sb + OFF_FIN + 256 + ch * 32), gb1 = ldsf4(sb + OFF_FIN + 256 + ch * 32 + 16);
        const float4 v0 = ldsf4(sb + OFF_FIN + 768 + ch * 32), v1 = ldsf4(sb + OFF_FIN + 768 + ch * 32 + 16);
        float v[8] = {v0.x, v0.y, v0.z, v0.w, v1.x, v1.y, v1.z, v1.w};
#pragma unroll
        for (int s = 0; s < 4; s++) {
          const uint4 u = lds128(sb + OFF_PIN4 + s * 4096 + off);
          v[0] += blo(u.x); v[1] += bhi(u.x); v[2] += blo(u.y); v[3] += bhi(u.y);
          v[4] += blo(u.z); v[5] += bhi(u.z); v[6] += blo(u.w); v[7] += bhi(u.w);
        }
        const uint4 xv = lds128(sb + 9 * 16384 + p * 4096 + off);
        uint4 o;
        o.x = pack2(fmaf(gb0.x, v[0], blo(xv.x)), fmaf(gb0.y, v[1], bhi(xv.x))); o.y = pack2(fmaf(gb0.z, v[2], blo(xv.y)), fmaf(gb0.w, v[3], bhi(xv.y)));
        o.z = pack2(fmaf(gb1.x, v[4], blo(xv.z)), fmaf(gb1.y, v[5], bhi(xv.z))); o.w = pack2(fmaf(gb1.z, v[6], blo(xv.w)), fmaf(gb1.w, v[7], bhi(xv.w)));
        *reinterpret_cast<uint4*>(out + (size_t)(128 * rb + 32 * p + r) * DM + 320 * hf + 256 + 8 * ch) = o;
      }
      {
        const uint32_t idv = (gq >> 1) == q ? ((gq & 1) ? 0x3F800000u : 0x00003F80u) : 0u;
        uint32_t idf[16];
#pragma unroll
        for (int ks = 0; ks < 4; ks++) { idf[4 * ks] = idf[4 * ks + 3] = (ks == w4 ? idv : 0u); idf[4 * ks + 1] = idf[4 * ks + 2] = 0u; }
        fence_regs(idf);
        const uint64_t dp = mkdesc(sb + OFF_PIN + wg * 8192, 16, 1024, 1);
#pragma unroll 1
        for (int s = 0; s < 3; s++) {
          mbar_wait(bars + 8 * (B_PIN + s), 0);
          if (s == 2 && stamp) STAMP(28 + wg);
          wg_fence();
#pragma unroll
          for (int ks = 0; ks < 4; ks++) wgmma_rs_n64(accA, &idf[4 * ks], dp + s * 1024 + ks * 128, 1);
          wg_commit();
        }
      }
      uint32_t xv[4][4];
#pragma unroll
      for (int j = 0; j < 4; j++) ldsm4(xv[j], sb + 8 * 16384 + rowaddr + (c0 ^ (32 * j)));
      wg_wait<0>();
      fence_regs(accA);
      if (stamp) STAMP(26 + wg);
#pragma unroll
      for (int j = 0; j < 4; j++) {
        const float2 t0 = ldsf2(sb + OFF_FIN + (16 * j + 2 * q) * 4), t1 = ldsf2(sb + OFF_FIN + (16 * j + 8 + 2 * q) * 4);
        stsm4(sb + 8 * 16384 + rowaddr + (c0 ^ (32 * j)),
              pack2(fmaf(t0.x, accA[8 * j], blo(xv[j][0])), fmaf(t0.y, accA[8 * j + 1], bhi(xv[j][0]))),
              pack2(fmaf(t0.x, accA[8 * j + 2], blo(xv[j][1])), fmaf(t0.y, accA[8 * j + 3], bhi(xv[j][1]))),
              pack2(fmaf(t1.x, accA[8 * j + 4], blo(xv[j][2])), fmaf(t1.y, accA[8 * j + 5], bhi(xv[j][2]))),
              pack2(fmaf(t1.x, accA[8 * j + 6], blo(xv[j][3])), fmaf(t1.y, accA[8 * j + 7], bhi(xv[j][3]))));
      }
      fence_async_smem();
      if (stamp) STAMP(30 + wg);
      __syncwarp();
      if (lane == 0) mbar_arrive(bars + 8 * B_OUTSTG);
    }
  }
}

typedef CUresult (*EncodeFn)(CUtensorMap*, CUtensorMapDataType, cuuint32_t, void*, const cuuint64_t*, const cuuint64_t*, const cuuint32_t*,
                             const cuuint32_t*, CUtensorMapInterleave, CUtensorMapSwizzle, CUtensorMapL2promotion, CUtensorMapFloatOOBfill);

void encode(EncodeFn fn, CUtensorMap* m, const void* ptr, int rank, const cuuint64_t* dims, const cuuint64_t* strides, const cuuint32_t* box,
            CUtensorMapSwizzle sw) {
  cuuint32_t es[5] = {1, 1, 1, 1, 1};
  fn(m, CU_TENSOR_MAP_DATA_TYPE_BFLOAT16, rank, const_cast<void*>(ptr), dims, strides, box, es, CU_TENSOR_MAP_INTERLEAVE_NONE, sw,
     CU_TENSOR_MAP_L2_PROMOTION_L2_128B, CU_TENSOR_MAP_FLOAT_OOB_FILL_NONE);
}

}

extern "C" void kernel_launch(void* const* d_in, const int* in_sizes, int n_in, void* d_out, int out_size) {
  (void)in_sizes; (void)n_in; (void)out_size;
  const __nv_bfloat16* x = (const __nv_bfloat16*)d_in[0];
  const __nv_bfloat16* wqkv = (const __nv_bfloat16*)d_in[1];
  const __nv_bfloat16* wo = (const __nv_bfloat16*)d_in[2];
  const __nv_bfloat16* w1 = (const __nv_bfloat16*)d_in[4];
  const __nv_bfloat16* b1 = (const __nv_bfloat16*)d_in[5];
  const __nv_bfloat16* w2 = (const __nv_bfloat16*)d_in[6];
  const __nv_bfloat16* b2 = (const __nv_bfloat16*)d_in[7];
  const __nv_bfloat16* cvec = (const __nv_bfloat16*)d_in[8];
  const __nv_bfloat16* wmod = (const __nv_bfloat16*)d_in[9];
  __nv_bfloat16* out = (__nv_bfloat16*)d_out;

  void* fp = nullptr;
  cudaDriverEntryPointQueryResult qr;
  cudaGetDriverEntryPoint("cuTensorMapEncodeTiled", &fp, cudaEnableDefault, &qr);
  EncodeFn fn = (EncodeFn)fp;
  void* ps = nullptr;
  cudaGetSymbolAddress(&ps, g_s);
  Scratch* gs = (Scratch*)ps;
  void *po = gs->o, *px1 = gs->x1;

  Maps m;
  {
    const cuuint64_t d[2] = {640, 2048}, s[1] = {1280};
    const cuuint32_t bt[2] = {64, 128}, bo[2] = {40, 128}, bx[2] = {80, 128};
    encode(fn, &m.x, x, 2, d, s, bt, CU_TENSOR_MAP_SWIZZLE_128B);
    encode(fn, &m.oLd, po, 2, d, s, bt, CU_TENSOR_MAP_SWIZZLE_128B);
    encode(fn, &m.oSt, po, 2, d, s, bo, CU_TENSOR_MAP_SWIZZLE_NONE);
    encode(fn, &m.x1Ld, px1, 2, d, s, bt, CU_TENSOR_MAP_SWIZZLE_128B);
    const cuuint32_t bw[2] = {80, 16};
    encode(fn, &m.x1St, px1, 2, d, s, bw, CU_TENSOR_MAP_SWIZZLE_NONE);
    encode(fn, &m.out, out, 2, d, s, bt, CU_TENSOR_MAP_SWIZZLE_128B);
    encode(fn, &m.xOwn, x, 2, d, s, bx, CU_TENSOR_MAP_SWIZZLE_NONE);
  }
  {
    const cuuint64_t d[2] = {3840, 640}, s[1] = {7680};
    const cuuint32_t bx[2] = {64, 160};
    encode(fn, &m.wmod, wmod, 2, d, s, bx, CU_TENSOR_MAP_SWIZZLE_128B);
    const cuuint32_t bx2[2] = {32, 160};
    encode(fn, &m.wmod2, wmod, 2, d, s, bx2, CU_TENSOR_MAP_SWIZZLE_64B);
  }
  {
    const cuuint64_t d[3] = {640, 640, 3}, s[2] = {3840, 1280};
    const cuuint32_t b128[3] = {64, 32, 3}, b32[3] = {16, 32, 3};
    encode(fn, &m.wqkv128, wqkv, 3, d, s, b128, CU_TENSOR_MAP_SWIZZLE_128B);
    encode(fn, &m.wqkv32, wqkv, 3, d, s, b32, CU_TENSOR_MAP_SWIZZLE_32B);
    const cuuint64_t d4[4] = {640, 640, 2, 3}, s4[3] = {3840, 64, 1280};
    const cuuint32_t b64[4] = {32, 32, 2, 3};
    encode(fn, &m.wqkv64, wqkv, 4, d4, s4, b64, CU_TENSOR_MAP_SWIZZLE_64B);
  }
  {
    const cuuint64_t d[4] = {640, 40, 8, 2}, s[3] = {1280, 80 * 1280, 40 * 1280};
    const cuuint32_t bx[4] = {16, 40, 8, 2};
    encode(fn, &m.wo, wo, 4, d, s, bx, CU_TENSOR_MAP_SWIZZLE_32B);
  }
  {
    const cuuint64_t d[3] = {64, 640, 27}, s[2] = {3456, 128};
    const cuuint32_t bx[3] = {64, 32, 3};
    encode(fn, &m.w1a, w1, 3, d, s, bx, CU_TENSOR_MAP_SWIZZLE_128B);
    const cuuint64_t d2[2] = {1728, 640}, s2[1] = {3456};
    const cuuint32_t bx2[2] = {32, 32};
    encode(fn, &m.w1b, w1, 2, d2, s2, bx2, CU_TENSOR_MAP_SWIZZLE_64B);
  }
  {
    const cuuint64_t d[2] = {640, 1728}, s[1] = {1280};
    const cuuint32_t bx[2] = {64, 224};
    encode(fn, &m.w2, w2, 2, d, s, bx, CU_TENSOR_MAP_SWIZZLE_128B);
  }
  cudaFuncSetAttribute(fused_block_kernel, cudaFuncAttributeMaxDynamicSharedMemorySize, SMEM_BYTES);
  fused_block_kernel<<<128, 384, SMEM_BYTES>>>(wmod, cvec, gs, x, wqkv, wo, w1, b1, w2, b2, out, m);
}
```
